```python
import torch

def _softmax(x, axis=-1):
    return torch.softmax(x, dim=axis)

def _gelu(x):
    return torch.nn.functional.gelu(x, approximate='tanh')

def _silu(x):
    return torch.nn.functional.silu(x)

def _sigmoid(x):
    return torch.sigmoid(x)

def _layernorm(x, axis=-1, eps=1e-05):
    m = x.mean(dim=axis, keepdim=True)
    v = x.var(dim=axis, keepdim=True, unbiased=False)
    return (x - m) / torch.sqrt(v + eps)

def _scatter_add(tgt, idx, src, axis=0):
    return tgt.clone().index_add_(axis, idx, src)

def _segment_sum(src, seg, n):
    out = torch.zeros((n,) + src.shape[1:], dtype=src.dtype)
    return out.index_add_(0, seg, src)

def _pad(x, pw):
    flat = tuple((v for pair in reversed(pw) for v in pair))
    return torch.nn.functional.pad(x, flat)
kernel_name = 'adaLN_cond__mha_block_cached__mixer_s_mlp__prompt'

def setup_inputs():

    _w = lambda a: (lambda t: t.to(torch.bfloat16) if t.is_floating_point() else t)(torch.as_tensor(a))

    def _A_setup():
        B, Sq, D = (1, 2048, 640)
        H, Sk, Dh = (32, 2048, 192)
        return {'x': _w((lambda *s: torch.randn(*s, dtype=torch.bfloat16) * 0.1)(B, Sq, D)), 'k_cache': _w((lambda *s: torch.randn(*s, dtype=torch.bfloat16) * 0.8)(B, H, Sk, Dh)), 'v_cache': _w((lambda *s: torch.randn(*s, dtype=torch.bfloat16) * 0.8)(B, H, Sk, Dh)), 'wq': _w((lambda *s: torch.randn(*s, dtype=torch.bfloat16) * 0.8)(D, H * Dh) * D ** (-0.5)), 'wo': _w((lambda *s: torch.randn(*s, dtype=torch.bfloat16) * 0.8)(H * Dh, D) * (H * Dh) ** (-0.5))}
    _A_in = _A_setup()

    def _B_setup():
        B, S, D, F = (1, 2048, 640, 1536)
        return {'x': _w((lambda *s: torch.randn(*s, dtype=torch.bfloat16) * 0.1)(B, S, D)), 'w1': _w((lambda *s: torch.randn(*s, dtype=torch.bfloat16) * 3.2)(D, D) * D ** (-0.5)), 'w2': _w((lambda *s: torch.randn(*s, dtype=torch.bfloat16) * 3.2)(D, D) * D ** (-0.5)), 'w3': _w((lambda *s: torch.randn(*s, dtype=torch.bfloat16) * 3.2)(D, F) * D ** (-0.5)), 'w4': _w((lambda *s: torch.randn(*s, dtype=torch.bfloat16) * 3.2)(F, D) * F ** (-0.5))}
    _B_in = _B_setup()
    return {'A_x': _A_in['x'], 'A_k_cache': _A_in['k_cache'], 'A_v_cache': _A_in['v_cache'], 'A_wq': _A_in['wq'], 'A_wo': _A_in['wo'], 'B_x': _B_in['x'], 'B_w1': _B_in['w1'], 'B_w2': _B_in['w2'], 'B_w3': _B_in['w3'], 'B_w4': _B_in['w4'], 'c': _w((lambda *s: torch.randn(*s, dtype=torch.bfloat16) * 0.2)(1, 640) * 8.0), 'w_mod': _w((lambda *s: torch.randn(*s, dtype=torch.bfloat16) * 0.2)(640, 6 * 640) * 640 ** (-0.5) * 8.0)}

def reference(A_x, A_k_cache, A_v_cache, A_wq, A_wo, B_x, B_w1, B_w2, B_w3, B_w4, c, w_mod):

    def _A_ref(x, k_cache, v_cache, wq, wo):
        B, Sq, D = x.shape
        H, Dh = (32, 192)
        q = (lambda x, *d: x.permute(*d))((x @ wq).reshape(B, Sq, H, Dh), 0, 2, 1, 3)
        scores = torch.einsum('bhqd,bhkd->bhqk', q, k_cache) * Dh ** (-0.5)
        p = _softmax(scores, axis=-1)
        o = torch.einsum('bhqk,bhkd->bhqd', p, v_cache)
        return (lambda x, *d: x.permute(*d))(o, 0, 2, 1, 3).reshape(B, Sq, H * Dh) @ wo

    def _B_ref(x, w1, w2, w3, w4):
        B, S, D = x.shape
        h = _gelu(_layernorm(x, axis=-1) @ w1)
        c = D // 4
        g0 = _pad(h[:, :, 0 * c:1 * c], ((0, 0), (1, 0), (0, 0)))[:, :S, :]
        g1 = _pad(h[:, :, 1 * c:2 * c], ((0, 0), (0, 1), (0, 0)))[:, 1:, :]
        g2 = _pad(h[:, :, 2 * c:3 * c], ((0, 0), (2, 0), (0, 0)))[:, :S, :]
        g3 = _pad(h[:, :, 3 * c:], ((0, 0), (0, 2), (0, 0)))[:, 2:, :]
        hs = torch.concatenate([g0, g1, g2, g3], axis=-1) @ w2
        x1 = x + hs
        h2 = _gelu(_layernorm(x1, axis=-1) @ w3) @ w4
        return x1 + h2
    x = A_x
    mod = (_silu(c) @ w_mod).reshape(c.shape[0], 6, 1, -1)
    sa, ca, ga, sb, cb, gb = (mod[:, 0].clone(), mod[:, 1].clone(), mod[:, 2].clone(), mod[:, 3].clone(), mod[:, 4].clone(), mod[:, 5].clone())
    h = _layernorm(x, axis=-1) * (1 + ca) + sa
    x = x + ga * _A_ref(h, A_k_cache, A_v_cache, A_wq, A_wo)
    h = _layernorm(x, axis=-1) * (1 + cb) + sb
    x = x + gb * _B_ref(h, B_w1, B_w2, B_w3, B_w4)
    return x
```

```cpp
#include <cuda_runtime.h>
#include <cuda_bf16.h>
#include <cuda.h>
#include <stdint.h>

typedef __nv_bfloat16 bf16;

constexpr int SEQ = 2048, DM = 640, NH = 32, DH = 192, FF = 1536;
constexpr int SLOT = 24576;
constexpr int NSLOT = 9;

__device__ __align__(16) uint32_t g_modp[DM / 2 * 4];
__device__ __align__(16) uint32_t g_modc[2 * DM];
__device__ __align__(128) int g_cnt2[49 * 32];
__device__ __align__(128) int g_cnt3[16 * 32];
__device__ __align__(1024) bf16 g_h[SEQ * DM];
__device__ __align__(1024) float g_acc[SEQ * DM];
__device__ __align__(1024) unsigned char g_stash[128 * 6 * SLOT];
__device__ __align__(128) float g_st2[SEQ * 2];
__device__ __align__(1024) bf16 g_t[SEQ * DM];
__device__ __align__(1024) bf16 g_g[(SEQ + 4) * DM];
__device__ __align__(1024) bf16 g_x1[SEQ * DM];
__device__ __align__(1024) unsigned char g_w1t[8 * 10 * 10240];
__device__ __align__(1024) unsigned char g_w2t[8 * 10 * 10240];
__device__ __align__(1024) unsigned char g_w4t[8 * 24 * 10240];
__device__ __align__(16) float g_cs3[FF];
__device__ __align__(1024) float g_stats[8 * SEQ * 2];
__device__ __align__(128) int g_flag[4 * 32 * 8];
__device__ __align__(1024) bf16 g_h2[SEQ * FF];
__device__ __forceinline__ uint32_t smem_u32(const void* p) { return (uint32_t)__cvta_generic_to_shared(p); }
__device__ __forceinline__ void mbar_init(uint32_t bar, int cnt) { asm volatile("mbarrier.init.shared.b64 [%0], %1;" ::"r"(bar), "r"(cnt) : "memory"); }
__device__ __forceinline__ void mbar_arrive(uint32_t bar) { asm volatile("mbarrier.arrive.shared.b64 _, [%0];" ::"r"(bar) : "memory"); }
__device__ __forceinline__ void mbar_expect_tx(uint32_t bar, int bytes) { asm volatile("mbarrier.arrive.expect_tx.shared.b64 _, [%0], %1;" ::"r"(bar), "r"(bytes) : "memory"); }
__device__ __forceinline__ void mbar_wait(uint32_t bar, uint32_t parity) {
  asm volatile(
      "{\n.reg .pred p;\n.reg .u32 c;\n"
      "mov.u32 c, 0;\n"
      "WAIT_%=:\n"
      "mbarrier.try_wait.parity.shared.b64 p, [%0], %1;\n"
      "@p bra DONE_%=;\n"
      "add.u32 c, c, 1;\n"
      "setp.lt.u32 p, c, 0x400000;\n"
      "@p bra WAIT_%=;\n"
      "trap;\n"
      "DONE_%=:\n}\n" ::"r"(bar), "r"(parity) : "memory");
}
__device__ __forceinline__ bool mbar_test(uint32_t bar, uint32_t parity) {
  uint32_t ok;
  asm volatile("{\n.reg .pred p;\nmbarrier.test_wait.parity.shared.b64 p, [%1], %2;\nselp.u32 %0, 1, 0, p;\n}\n"
               : "=r"(ok) : "r"(bar), "r"(parity) : "memory");
  return ok != 0;
}
__device__ __forceinline__ void fence_proxy_async_gmem() { asm volatile("fence.proxy.async.global;" ::: "memory"); }
__device__ __forceinline__ void pdl_wait() { asm volatile("griddepcontrol.wait;" ::: "memory"); }
__device__ __forceinline__ void pdl_trigger() { asm volatile("griddepcontrol.launch_dependents;" ::: "memory"); }
__device__ __forceinline__ void fence_proxy_async_smem() { asm volatile("fence.proxy.async.shared::cta;" ::: "memory"); }
__device__ __forceinline__ void tma_2d(uint32_t dst, const CUtensorMap* tm, uint32_t bar, int c0, int c1) {
  asm volatile("cp.async.bulk.tensor.2d.shared::cluster.global.mbarrier::complete_tx::bytes [%0], [%1, {%3, %4}], [%2];"
               ::"r"(dst), "l"(tm), "r"(bar), "r"(c0), "r"(c1) : "memory");
}
__device__ __forceinline__ void tma_3d(uint32_t dst, const CUtensorMap* tm, uint32_t bar, int c0, int c1, int c2) {
  asm volatile("cp.async.bulk.tensor.3d.shared::cluster.global.mbarrier::complete_tx::bytes [%0], [%1, {%3, %4, %5}], [%2];"
               ::"r"(dst), "l"(tm), "r"(bar), "r"(c0), "r"(c1), "r"(c2) : "memory");
}
__device__ __forceinline__ void tma_2d_mc(uint32_t dst, const CUtensorMap* tm, uint32_t bar, int c0, int c1) {
  asm volatile("cp.async.bulk.tensor.2d.shared::cluster.global.mbarrier::complete_tx::bytes.multicast::cluster [%0], [%1, {%3, %4}], [%2], %5;"
               ::"r"(dst), "l"(tm), "r"(bar), "r"(c0), "r"(c1), "h"((uint16_t)3) : "memory");
}
__device__ __forceinline__ void tma_3d_mc(uint32_t dst, const CUtensorMap* tm, uint32_t bar, int c0, int c1, int c2) {
  asm volatile("cp.async.bulk.tensor.3d.shared::cluster.global.mbarrier::complete_tx::bytes.multicast::cluster [%0], [%1, {%3, %4, %5}], [%2], %6;"
               ::"r"(dst), "l"(tm), "r"(bar), "r"(c0), "r"(c1), "r"(c2), "h"((uint16_t)3) : "memory");
}
__device__ __forceinline__ void tma_prefetch_2d(const CUtensorMap* tm, int c0, int c1) {
  asm volatile("cp.async.bulk.prefetch.tensor.2d.L2.global [%0, {%1, %2}];" ::"l"(tm), "r"(c0), "r"(c1) : "memory");
}
__device__ __forceinline__ void tma_prefetch_3d(const CUtensorMap* tm, int c0, int c1, int c2) {
  asm volatile("cp.async.bulk.prefetch.tensor.3d.L2.global [%0, {%1, %2, %3}];" ::"l"(tm), "r"(c0), "r"(c1), "r"(c2) : "memory");
}
__device__ __forceinline__ void prefetch_tmap(const CUtensorMap* tm) { asm volatile("prefetch.tensormap [%0];" ::"l"(tm) : "memory"); }
__device__ __forceinline__ void flag_add(int* c) { asm volatile("red.relaxed.gpu.global.add.s32 [%0], 1;" ::"l"(c) : "memory"); }
__device__ __forceinline__ int flag_ld(const int* c) {
  int v; asm volatile("ld.relaxed.gpu.global.s32 %0, [%1];" : "=r"(v) : "l"(c) : "memory"); return v;
}
__device__ __forceinline__ void l2_prefetch(const void* p, int bytes) {
  asm volatile("cp.async.bulk.prefetch.L2.global [%0], %1;" ::"l"(p), "r"(bytes) : "memory");
}
__device__ __forceinline__ uint32_t mapa(uint32_t addr, uint32_t cta) {
  uint32_t r; asm("mapa.shared::cluster.u32 %0, %1, %2;" : "=r"(r) : "r"(addr), "r"(cta)); return r;
}
__device__ __forceinline__ void mbar_arrive_cluster(uint32_t bar) { asm volatile("mbarrier.arrive.shared::cluster.b64 _, [%0];" ::"r"(bar) : "memory"); }
__device__ __forceinline__ void cluster_sync() {
  asm volatile("barrier.cluster.arrive.relaxed.aligned;\nbarrier.cluster.wait.aligned;" ::: "memory");
}
__device__ __forceinline__ void bulk_g2s(uint32_t dst, const void* src, int bytes, uint32_t bar) {
  asm volatile("cp.async.bulk.shared::cluster.global.mbarrier::complete_tx::bytes [%0], [%1], %2, [%3];"
               ::"r"(dst), "l"(src), "r"(bytes), "r"(bar) : "memory");
}
__device__ __forceinline__ void bulk_s2g(void* dst, uint32_t src, int bytes) {
  asm volatile("cp.async.bulk.global.shared::cta.bulk_group [%0], [%1], %2;" ::"l"(dst), "r"(src), "r"(bytes) : "memory");
}
__device__ __forceinline__ void bulk_commit() { asm volatile("cp.async.bulk.commit_group;" ::: "memory"); }
template <int N> __device__ __forceinline__ void bulk_wait_read() { asm volatile("cp.async.bulk.wait_group.read %0;" ::"n"(N) : "memory"); }
template <int N> __device__ __forceinline__ void bulk_wait() { asm volatile("cp.async.bulk.wait_group %0;" ::"n"(N) : "memory"); }
__device__ __forceinline__ void wg_fence() { asm volatile("wgmma.fence.sync.aligned;" ::: "memory"); }
__device__ __forceinline__ void wg_commit() { asm volatile("wgmma.commit_group.sync.aligned;" ::: "memory"); }
template <int N> __device__ __forceinline__ void wg_wait() { asm volatile("wgmma.wait_group.sync.aligned %0;" ::"n"(N) : "memory"); }
__device__ __forceinline__ void bar_sync(int id, int n) { asm volatile("bar.sync %0, %1;" ::"r"(id), "r"(n) : "memory"); }
__device__ __forceinline__ void bar_arrive(int id, int n) { asm volatile("bar.arrive %0, %1;" ::"r"(id), "r"(n) : "memory"); }
template <int N> __device__ __forceinline__ void fence_regs(float (&r)[N]) {
#pragma unroll
  for (int i = 0; i < N; i++) asm volatile("" : "+f"(r[i])::"memory");
}
template <int N> __device__ __forceinline__ void fence_regs_u(uint32_t (&r)[N]) {
#pragma unroll
  for (int i = 0; i < N; i++) asm volatile("" : "+r"(r[i])::"memory");
}
__device__ __forceinline__ uint32_t mkdesc(uint32_t addr, uint32_t lbo) { return ((addr & 0x3FFFF) >> 4) | ((lbo >> 4) << 16); }
__device__ __forceinline__ uint32_t pack_bf16(float lo, float hi) {
  uint32_t r;
  asm("cvt.rn.bf16x2.f32 %0, %1, %2;" : "=r"(r) : "f"(hi), "f"(lo));
  return r;
}
__device__ __forceinline__ float bf16r(float x) { return __bfloat162float(__float2bfloat16_rn(x)); }
__device__ __forceinline__ float bf_lo(uint32_t u) { return __uint_as_float(u << 16); }
__device__ __forceinline__ float bf_hi(uint32_t u) { return __uint_as_float(u & 0xffff0000u); }
__device__ __forceinline__ float ex2(float x) { float y; asm("ex2.approx.ftz.f32 %0, %1;" : "=f"(y) : "f"(x)); return y; }
__device__ __forceinline__ float gelu_tanh(float x) {
  const float u = x * fmaf(x * x, 0.0356774081363001f, 0.7978845608028654f);
  float t; asm("tanh.approx.f32 %0, %1;" : "=f"(t) : "f"(u));
  const float hx = 0.5f * x;
  return fmaf(hx, t, hx);
}
__device__ __forceinline__ uint32_t gelu_pair(float a, float b) {
  const uint32_t r = pack_bf16(a, b);
  return pack_bf16(gelu_tanh(bf_lo(r)), gelu_tanh(bf_hi(r)));
}
__device__ __forceinline__ void stmatrix_x4(uint32_t addr, uint32_t r0, uint32_t r1, uint32_t r2, uint32_t r3) {
  asm volatile("stmatrix.sync.aligned.m8n8.x4.shared.b16 [%0], {%1, %2, %3, %4};" ::"r"(addr), "r"(r0), "r"(r1), "r"(r2), "r"(r3) : "memory");
}
__device__ __forceinline__ void red_add_v4(float* p, float a, float b, float c, float d) {
  asm volatile("red.global.add.v4.f32 [%0], {%1, %2, %3, %4};" ::"l"(p), "f"(a), "f"(b), "f"(c), "f"(d) : "memory");
}

__device__ __forceinline__ void wgmma_m64n160k16_ss_tb0(float (&d)[80], uint32_t descA, uint32_t descB, int scaleD) {
  asm volatile("{\n.reg .pred p;\n.reg .b64 da, db;\n"
    "setp.ne.b32 p, %82, 0;\n"
    "mov.b64 da, {%80, 0x40000040};\n"
    "mov.b64 db, {%81, 0x40000040};\n"
    "wgmma.mma_async.sync.aligned.m64n160k16.f32.bf16.bf16 "
    "{%0, %1, %2, %3, %4, %5, %6, %7, %8, %9, %10, %11, %12, %13, %14, %15, %16, %17, %18, %19, %20, %21, %22, %23, %24, %25, %26, %27, %28, %29, %30, %31, %32, %33, %34, %35, %36, %37, %38, %39, %40, %41, %42, %43, %44, %45, %46, %47, %48, %49, %50, %51, %52, %53, %54, %55, %56, %57, %58, %59, %60, %61, %62, %63, %64, %65, %66, %67, %68, %69, %70, %71, %72, %73, %74, %75, %76, %77, %78, %79}, "
    "da, db, p, 1, 1, 0, 0;\n}\n"
    : "+f"(d[0]), "+f"(d[1]), "+f"(d[2]), "+f"(d[3]), "+f"(d[4]), "+f"(d[5]), "+f"(d[6]), "+f"(d[7]), "+f"(d[8]), "+f"(d[9]), "+f"(d[10]), "+f"(d[11]), "+f"(d[12]), "+f"(d[13]), "+f"(d[14]), "+f"(d[15]), "+f"(d[16]), "+f"(d[17]), "+f"(d[18]), "+f"(d[19]), "+f"(d[20]), "+f"(d[21]), "+f"(d[22]), "+f"(d[23]), "+f"(d[24]), "+f"(d[25]), "+f"(d[26]), "+f"(d[27]), "+f"(d[28]), "+f"(d[29]), "+f"(d[30]), "+f"(d[31]), "+f"(d[32]), "+f"(d[33]), "+f"(d[34]), "+f"(d[35]), "+f"(d[36]), "+f"(d[37]), "+f"(d[38]), "+f"(d[39]), "+f"(d[40]), "+f"(d[41]), "+f"(d[42]), "+f"(d[43]), "+f"(d[44]), "+f"(d[45]), "+f"(d[46]), "+f"(d[47]), "+f"(d[48]), "+f"(d[49]), "+f"(d[50]), "+f"(d[51]), "+f"(d[52]), "+f"(d[53]), "+f"(d[54]), "+f"(d[55]), "+f"(d[56]), "+f"(d[57]), "+f"(d[58]), "+f"(d[59]), "+f"(d[60]), "+f"(d[61]), "+f"(d[62]), "+f"(d[63]), "+f"(d[64]), "+f"(d[65]), "+f"(d[66]), "+f"(d[67]), "+f"(d[68]), "+f"(d[69]), "+f"(d[70]), "+f"(d[71]), "+f"(d[72]), "+f"(d[73]), "+f"(d[74]), "+f"(d[75]), "+f"(d[76]), "+f"(d[77]), "+f"(d[78]), "+f"(d[79])
    : "r"(descA), "r"(descB), "r"(scaleD));
}
__device__ __forceinline__ void wgmma_m64n192k16_rs_tb1(float (&d)[96], uint32_t a0, uint32_t a1, uint32_t a2, uint32_t a3, uint32_t descB, int scaleD) {
  asm volatile("{\n.reg .pred p;\n.reg .b64 da, db;\n"
    "setp.ne.b32 p, %101, 0;\n"
    "mov.b64 db, {%100, 0x40000040};\n"
    "wgmma.mma_async.sync.aligned.m64n192k16.f32.bf16.bf16 "
    "{%0, %1, %2, %3, %4, %5, %6, %7, %8, %9, %10, %11, %12, %13, %14, %15, %16, %17, %18, %19, %20, %21, %22, %23, %24, %25, %26, %27, %28, %29, %30, %31, %32, %33, %34, %35, %36, %37, %38, %39, %40, %41, %42, %43, %44, %45, %46, %47, %48, %49, %50, %51, %52, %53, %54, %55, %56, %57, %58, %59, %60, %61, %62, %63, %64, %65, %66, %67, %68, %69, %70, %71, %72, %73, %74, %75, %76, %77, %78, %79, %80, %81, %82, %83, %84, %85, %86, %87, %88, %89, %90, %91, %92, %93, %94, %95}, "
    "{%96, %97, %98, %99}, db, p, 1, 1, 1;\n}\n"
    : "+f"(d[0]), "+f"(d[1]), "+f"(d[2]), "+f"(d[3]), "+f"(d[4]), "+f"(d[5]), "+f"(d[6]), "+f"(d[7]), "+f"(d[8]), "+f"(d[9]), "+f"(d[10]), "+f"(d[11]), "+f"(d[12]), "+f"(d[13]), "+f"(d[14]), "+f"(d[15]), "+f"(d[16]), "+f"(d[17]), "+f"(d[18]), "+f"(d[19]), "+f"(d[20]), "+f"(d[21]), "+f"(d[22]), "+f"(d[23]), "+f"(d[24]), "+f"(d[25]), "+f"(d[26]), "+f"(d[27]), "+f"(d[28]), "+f"(d[29]), "+f"(d[30]), "+f"(d[31]), "+f"(d[32]), "+f"(d[33]), "+f"(d[34]), "+f"(d[35]), "+f"(d[36]), "+f"(d[37]), "+f"(d[38]), "+f"(d[39]), "+f"(d[40]), "+f"(d[41]), "+f"(d[42]), "+f"(d[43]), "+f"(d[44]), "+f"(d[45]), "+f"(d[46]), "+f"(d[47]), "+f"(d[48]), "+f"(d[49]), "+f"(d[50]), "+f"(d[51]), "+f"(d[52]), "+f"(d[53]), "+f"(d[54]), "+f"(d[55]), "+f"(d[56]), "+f"(d[57]), "+f"(d[58]), "+f"(d[59]), "+f"(d[60]), "+f"(d[61]), "+f"(d[62]), "+f"(d[63]), "+f"(d[64]), "+f"(d[65]), "+f"(d[66]), "+f"(d[67]), "+f"(d[68]), "+f"(d[69]), "+f"(d[70]), "+f"(d[71]), "+f"(d[72]), "+f"(d[73]), "+f"(d[74]), "+f"(d[75]), "+f"(d[76]), "+f"(d[77]), "+f"(d[78]), "+f"(d[79]), "+f"(d[80]), "+f"(d[81]), "+f"(d[82]), "+f"(d[83]), "+f"(d[84]), "+f"(d[85]), "+f"(d[86]), "+f"(d[87]), "+f"(d[88]), "+f"(d[89]), "+f"(d[90]), "+f"(d[91]), "+f"(d[92]), "+f"(d[93]), "+f"(d[94]), "+f"(d[95])
    : "r"(a0), "r"(a1), "r"(a2), "r"(a3), "r"(descB), "r"(scaleD));
}
__device__ __forceinline__ void wgmma_m64n192k16_ss_tb1(float (&d)[96], uint32_t descA, uint32_t descB, int scaleD) {
  asm volatile("{\n.reg .pred p;\n.reg .b64 da, db;\n"
    "setp.ne.b32 p, %98, 0;\n"
    "mov.b64 da, {%96, 0x40000040};\n"
    "mov.b64 db, {%97, 0x40000040};\n"
    "wgmma.mma_async.sync.aligned.m64n192k16.f32.bf16.bf16 "
    "{%0, %1, %2, %3, %4, %5, %6, %7, %8, %9, %10, %11, %12, %13, %14, %15, %16, %17, %18, %19, %20, %21, %22, %23, %24, %25, %26, %27, %28, %29, %30, %31, %32, %33, %34, %35, %36, %37, %38, %39, %40, %41, %42, %43, %44, %45, %46, %47, %48, %49, %50, %51, %52, %53, %54, %55, %56, %57, %58, %59, %60, %61, %62, %63, %64, %65, %66, %67, %68, %69, %70, %71, %72, %73, %74, %75, %76, %77, %78, %79, %80, %81, %82, %83, %84, %85, %86, %87, %88, %89, %90, %91, %92, %93, %94, %95}, "
    "da, db, p, 1, 1, 0, 1;\n}\n"
    : "+f"(d[0]), "+f"(d[1]), "+f"(d[2]), "+f"(d[3]), "+f"(d[4]), "+f"(d[5]), "+f"(d[6]), "+f"(d[7]), "+f"(d[8]), "+f"(d[9]), "+f"(d[10]), "+f"(d[11]), "+f"(d[12]), "+f"(d[13]), "+f"(d[14]), "+f"(d[15]), "+f"(d[16]), "+f"(d[17]), "+f"(d[18]), "+f"(d[19]), "+f"(d[20]), "+f"(d[21]), "+f"(d[22]), "+f"(d[23]), "+f"(d[24]), "+f"(d[25]), "+f"(d[26]), "+f"(d[27]), "+f"(d[28]), "+f"(d[29]), "+f"(d[30]), "+f"(d[31]), "+f"(d[32]), "+f"(d[33]), "+f"(d[34]), "+f"(d[35]), "+f"(d[36]), "+f"(d[37]), "+f"(d[38]), "+f"(d[39]), "+f"(d[40]), "+f"(d[41]), "+f"(d[42]), "+f"(d[43]), "+f"(d[44]), "+f"(d[45]), "+f"(d[46]), "+f"(d[47]), "+f"(d[48]), "+f"(d[49]), "+f"(d[50]), "+f"(d[51]), "+f"(d[52]), "+f"(d[53]), "+f"(d[54]), "+f"(d[55]), "+f"(d[56]), "+f"(d[57]), "+f"(d[58]), "+f"(d[59]), "+f"(d[60]), "+f"(d[61]), "+f"(d[62]), "+f"(d[63]), "+f"(d[64]), "+f"(d[65]), "+f"(d[66]), "+f"(d[67]), "+f"(d[68]), "+f"(d[69]), "+f"(d[70]), "+f"(d[71]), "+f"(d[72]), "+f"(d[73]), "+f"(d[74]), "+f"(d[75]), "+f"(d[76]), "+f"(d[77]), "+f"(d[78]), "+f"(d[79]), "+f"(d[80]), "+f"(d[81]), "+f"(d[82]), "+f"(d[83]), "+f"(d[84]), "+f"(d[85]), "+f"(d[86]), "+f"(d[87]), "+f"(d[88]), "+f"(d[89]), "+f"(d[90]), "+f"(d[91]), "+f"(d[92]), "+f"(d[93]), "+f"(d[94]), "+f"(d[95])
    : "r"(descA), "r"(descB), "r"(scaleD));
}
__device__ __forceinline__ void wgmma_m64n64k16_rs_tb0(float (&d)[32], uint32_t a0, uint32_t a1, uint32_t a2, uint32_t a3, uint32_t descB, int scaleD) {
  asm volatile("{\n.reg .pred p;\n.reg .b64 da, db;\n"
    "setp.ne.b32 p, %37, 0;\n"
    "mov.b64 db, {%36, 0x40000040};\n"
    "wgmma.mma_async.sync.aligned.m64n64k16.f32.bf16.bf16 "
    "{%0, %1, %2, %3, %4, %5, %6, %7, %8, %9, %10, %11, %12, %13, %14, %15, %16, %17, %18, %19, %20, %21, %22, %23, %24, %25, %26, %27, %28, %29, %30, %31}, "
    "{%32, %33, %34, %35}, db, p, 1, 1, 0;\n}\n"
    : "+f"(d[0]), "+f"(d[1]), "+f"(d[2]), "+f"(d[3]), "+f"(d[4]), "+f"(d[5]), "+f"(d[6]), "+f"(d[7]), "+f"(d[8]), "+f"(d[9]), "+f"(d[10]), "+f"(d[11]), "+f"(d[12]), "+f"(d[13]), "+f"(d[14]), "+f"(d[15]), "+f"(d[16]), "+f"(d[17]), "+f"(d[18]), "+f"(d[19]), "+f"(d[20]), "+f"(d[21]), "+f"(d[22]), "+f"(d[23]), "+f"(d[24]), "+f"(d[25]), "+f"(d[26]), "+f"(d[27]), "+f"(d[28]), "+f"(d[29]), "+f"(d[30]), "+f"(d[31])
    : "r"(a0), "r"(a1), "r"(a2), "r"(a3), "r"(descB), "r"(scaleD));
}
__device__ __forceinline__ void wgmma_m64n64k16_rs_tb1(float (&d)[32], uint32_t a0, uint32_t a1, uint32_t a2, uint32_t a3, uint32_t descB, int scaleD) {
  asm volatile("{\n.reg .pred p;\n.reg .b64 da, db;\n"
    "setp.ne.b32 p, %37, 0;\n"
    "mov.b64 db, {%36, 0x40000040};\n"
    "wgmma.mma_async.sync.aligned.m64n64k16.f32.bf16.bf16 "
    "{%0, %1, %2, %3, %4, %5, %6, %7, %8, %9, %10, %11, %12, %13, %14, %15, %16, %17, %18, %19, %20, %21, %22, %23, %24, %25, %26, %27, %28, %29, %30, %31}, "
    "{%32, %33, %34, %35}, db, p, 1, 1, 1;\n}\n"
    : "+f"(d[0]), "+f"(d[1]), "+f"(d[2]), "+f"(d[3]), "+f"(d[4]), "+f"(d[5]), "+f"(d[6]), "+f"(d[7]), "+f"(d[8]), "+f"(d[9]), "+f"(d[10]), "+f"(d[11]), "+f"(d[12]), "+f"(d[13]), "+f"(d[14]), "+f"(d[15]), "+f"(d[16]), "+f"(d[17]), "+f"(d[18]), "+f"(d[19]), "+f"(d[20]), "+f"(d[21]), "+f"(d[22]), "+f"(d[23]), "+f"(d[24]), "+f"(d[25]), "+f"(d[26]), "+f"(d[27]), "+f"(d[28]), "+f"(d[29]), "+f"(d[30]), "+f"(d[31])
    : "r"(a0), "r"(a1), "r"(a2), "r"(a3), "r"(descB), "r"(scaleD));
}
__device__ __forceinline__ void wgmma_m64n64k16_ss_tb1(float (&d)[32], uint32_t descA, uint32_t descB, int scaleD) {
  asm volatile("{\n.reg .pred p;\n.reg .b64 da, db;\n"
    "setp.ne.b32 p, %34, 0;\n"
    "mov.b64 da, {%32, 0x40000040};\n"
    "mov.b64 db, {%33, 0x40000040};\n"
    "wgmma.mma_async.sync.aligned.m64n64k16.f32.bf16.bf16 "
    "{%0, %1, %2, %3, %4, %5, %6, %7, %8, %9, %10, %11, %12, %13, %14, %15, %16, %17, %18, %19, %20, %21, %22, %23, %24, %25, %26, %27, %28, %29, %30, %31}, "
    "da, db, p, 1, 1, 0, 1;\n}\n"
    : "+f"(d[0]), "+f"(d[1]), "+f"(d[2]), "+f"(d[3]), "+f"(d[4]), "+f"(d[5]), "+f"(d[6]), "+f"(d[7]), "+f"(d[8]), "+f"(d[9]), "+f"(d[10]), "+f"(d[11]), "+f"(d[12]), "+f"(d[13]), "+f"(d[14]), "+f"(d[15]), "+f"(d[16]), "+f"(d[17]), "+f"(d[18]), "+f"(d[19]), "+f"(d[20]), "+f"(d[21]), "+f"(d[22]), "+f"(d[23]), "+f"(d[24]), "+f"(d[25]), "+f"(d[26]), "+f"(d[27]), "+f"(d[28]), "+f"(d[29]), "+f"(d[30]), "+f"(d[31])
    : "r"(descA), "r"(descB), "r"(scaleD));
}
__device__ __forceinline__ void wgmma_m64n80k16_ss_tb0(float (&d)[40], uint32_t descA, uint32_t descB, int scaleD) {
  asm volatile("{\n.reg .pred p;\n.reg .b64 da, db;\n"
    "setp.ne.b32 p, %42, 0;\n"
    "mov.b64 da, {%40, 0x40000040};\n"
    "mov.b64 db, {%41, 0x40000040};\n"
    "wgmma.mma_async.sync.aligned.m64n80k16.f32.bf16.bf16 "
    "{%0, %1, %2, %3, %4, %5, %6, %7, %8, %9, %10, %11, %12, %13, %14, %15, %16, %17, %18, %19, %20, %21, %22, %23, %24, %25, %26, %27, %28, %29, %30, %31, %32, %33, %34, %35, %36, %37, %38, %39}, "
    "da, db, p, 1, 1, 0, 0;\n}\n"
    : "+f"(d[0]), "+f"(d[1]), "+f"(d[2]), "+f"(d[3]), "+f"(d[4]), "+f"(d[5]), "+f"(d[6]), "+f"(d[7]), "+f"(d[8]), "+f"(d[9]), "+f"(d[10]), "+f"(d[11]), "+f"(d[12]), "+f"(d[13]), "+f"(d[14]), "+f"(d[15]), "+f"(d[16]), "+f"(d[17]), "+f"(d[18]), "+f"(d[19]), "+f"(d[20]), "+f"(d[21]), "+f"(d[22]), "+f"(d[23]), "+f"(d[24]), "+f"(d[25]), "+f"(d[26]), "+f"(d[27]), "+f"(d[28]), "+f"(d[29]), "+f"(d[30]), "+f"(d[31]), "+f"(d[32]), "+f"(d[33]), "+f"(d[34]), "+f"(d[35]), "+f"(d[36]), "+f"(d[37]), "+f"(d[38]), "+f"(d[39])
    : "r"(descA), "r"(descB), "r"(scaleD));
}

__device__ __forceinline__ float silu_bf16(bf16 c) { const float v = __bfloat162float(c); return bf16r(__fdividef(v, 1.0f + __expf(-v))); }
__device__ __forceinline__ int fresh_ctaid() { int b; asm volatile("mov.u32 %0, %%ctaid.x;" : "=r"(b)); return b - 4; }
struct SideArgs { const bf16 *w_mod, *x, *c, *w1, *w2, *w3, *w4; };
constexpr int NSIDE = 4;
__device__ __noinline__ void side_work(const SideArgs& sa, unsigned char* smem) {
  const int tid = threadIdx.x, lane = tid & 31, warp = tid >> 5, cta = blockIdx.x, ht = cta * 384 + tid;
  const uint32_t sb = smem_u32(smem), bar = sb + 200704;
  float* sc = (float*)(smem + 196608);
  if (ht < 1024) g_flag[ht] = 0;
  else if (ht < 1040) g_cnt3[(ht - 1024) * 32] = 0;
  else if (ht >= 1056) {
    const int e = ht - 1056, pc = e / 80;
    const int row = pc == 0 ? 0 : pc == 1 ? SEQ - 1 : pc == 2 ? 0 : pc == 3 ? 1 : pc == 4 ? SEQ - 2 : SEQ - 1;
    const int g4 = pc == 0 ? 0 : pc == 1 ? 1 : pc < 4 ? 2 : 3;
    ((uint32_t*)(g_g + (size_t)(row + 2) * DM + g4 * 160))[e % 80] = 0u;
  }
  for (int i = tid; i < DM; i += 384) sc[i] = silu_bf16(sa.c[i]);
  if (tid == 0) {
    mbar_init(bar, 1); mbar_init(bar + 8, 1);
    for (uint32_t it = 0; flag_ld(g_cnt2 + 16 * 32) < 8; it++) { __nanosleep(200); if (it > (1u << 22)) __trap(); }
  }
  fence_proxy_async_smem();
  __syncthreads();
  auto job_src = [&](int j) { const int u = j * NSIDE + cta; return (u < 10 ? sa.w1 + u * 64 * DM : u < 20 ? sa.w2 + (u - 10) * 64 * DM : sa.w4 + (u - 20) * 64 * DM); };
  if (tid == 0) { mbar_expect_tx(bar, 81920); bulk_g2s(sb, job_src(0), 81920, bar); }
#pragma unroll 1
  for (int j = 0; j < 11; j++) {
    if (tid == 0 && j + 1 < 11) { mbar_expect_tx(bar + ((j + 1) & 1) * 8, 81920); bulk_g2s(sb + ((j + 1) & 1) * 81920, job_src(j + 1), 81920, bar + ((j + 1) & 1) * 8); }
    mbar_wait(bar + (j & 1) * 8, (j >> 1) & 1);
    if (warp < 8) {
      const int u = j * NSIDE + cta;
      unsigned char* dst = (u < 10 ? g_w1t + (size_t)(warp * 10 + u) * 10240 : u < 20 ? g_w2t + (size_t)(warp * 10 + u - 10) * 10240
                                                                             : g_w4t + (size_t)(warp * 24 + u - 20) * 10240) + (lane & 3) * 4;
      const uint4* src = (const uint4*)(smem + (j & 1) * 81920 + lane * 2560 + warp * 160);
      const int c = lane >> 2;
#pragma unroll 2
      for (int i = 0; i < 10; i++) {
        const uint4 r0 = src[i], r1 = src[80 + i];
#define SIDE_ST(j, f, sel) *(uint32_t*)(dst + i * 1024 + (j) * 128 + ((c ^ (j)) << 4)) = __byte_perm(r0.f, r1.f, sel)
        SIDE_ST(0, x, 0x5410); SIDE_ST(1, x, 0x7632); SIDE_ST(2, y, 0x5410); SIDE_ST(3, y, 0x7632);
        SIDE_ST(4, z, 0x5410); SIDE_ST(5, z, 0x7632); SIDE_ST(6, w, 0x5410); SIDE_ST(7, w, 0x7632);
#undef SIDE_ST
      }
    }
    __syncthreads();
  }
  float a0 = 0.f, a1 = 0.f, c0 = 0.f, c1 = 0.f;
#pragma unroll 1
  for (int k = 0; k < 16; k++) {
    for (int kk = (k == 0 ? 0 : k + 1); kk <= k + 1 && kk < 16; kk++) {
      const uint32_t bb = bar + ((kk + 1) & 1) * 8, d = sb + ((kk + 1) & 1) * 81920;
      if (tid == 0) mbar_expect_tx(bb, 81920);
      if (warp < 10 && lane < 4) {
        const int rr = warp * 4 + lane, r = kk * 40 + rr;
        bulk_g2s(d + rr * 1280, sa.w_mod + (size_t)r * (6 * DM) + (2 + cta) * DM, 1280, bb);
        bulk_g2s(d + 51200 + rr * 768, sa.w3 + (size_t)r * FF + cta * 384, 768, bb);
      }
    }
    __syncwarp();
    mbar_wait(bar + ((k + 1) & 1) * 8, ((11 + k) >> 1) & 1);
    const uint32_t* d = (const uint32_t*)(smem + ((k + 1) & 1) * 81920);
    if (tid < 320) {
#pragma unroll 8
      for (int r = 0; r < 40; r++) { const uint32_t u = d[r * 320 + tid]; const float f = sc[k * 40 + r]; a0 = fmaf(f, bf_lo(u), a0); a1 = fmaf(f, bf_hi(u), a1); }
    }
    if (tid >= 192) {
#pragma unroll 8
      for (int r = 0; r < 40; r++) { const uint32_t u = d[12800 + r * 192 + tid - 192]; c0 += bf_lo(u); c1 += bf_hi(u); }
    }
    __syncthreads();
  }
  if (tid < 320) {
    uint32_t v = pack_bf16(a0, a1);
    if (cta == 2) v = pack_bf16(1.0f + bf_lo(v), 1.0f + bf_hi(v));
    g_modp[tid * 4 + (cta == 0 ? 0 : cta == 1 ? 2 : cta == 2 ? 1 : 3)] = v;
  }
  if (tid >= 192) *(float2*)(g_cs3 + cta * 384 + (tid - 192) * 2) = make_float2(c0, c1);
  __threadfence();
  __syncthreads();
  if (tid == 0) atomicAdd(g_cnt2, 1);
}

#define CLUSTER 2
#define QT_OF(b) ((((b) >> 4) << 1) | ((b) & 1))
#define GRP_OF(b) (((b) >> 1) & 7)
struct Pipe {
  int slot; uint32_t phase;
  __device__ __forceinline__ void next() { if (++slot == NSLOT) { slot = 0; phase ^= 1; } }
};

constexpr int STAGE_OFF = NSLOT * SLOT;
constexpr int BAR_OFF = STAGE_OFF + 8192;
constexpr int ATT_SMEM = BAR_OFF + 256;
constexpr int FIN_BASE = 4 * 84;
constexpr int FIN_PIN = 4;
constexpr int FIN_RING = NSLOT - FIN_PIN;
__device__ __forceinline__ int fin_slot(int i) { return (FIN_BASE + i) % NSLOT; }
__device__ __forceinline__ uint32_t fin_round(int i) { return ((FIN_BASE + i) / NSLOT) & 1; }

__device__ __forceinline__ void ld_shared_3d(bool mine, uint32_t dst, const CUtensorMap* tm, uint32_t bar, int c0, int c1, int c2) {
  if (CLUSTER == 1) tma_3d(dst, tm, bar, c0, c1, c2);
  else if (mine) tma_3d_mc(dst, tm, bar, c0, c1, c2);
}
__device__ __forceinline__ void ld_shared_2d(bool mine, uint32_t dst, const CUtensorMap* tm, uint32_t bar, int c0, int c1) {
  if (CLUSTER == 1) tma_2d(dst, tm, bar, c0, c1);
  else if (mine) tma_2d_mc(dst, tm, bar, c0, c1);
}

__global__ void __cluster_dims__(CLUSTER, 1, 1) __launch_bounds__(384, 1)
attn_kernel(const __grid_constant__ SideArgs sa, const __grid_constant__ CUtensorMap tmH, const __grid_constant__ CUtensorMap tmWq,
            const __grid_constant__ CUtensorMap tmK, const __grid_constant__ CUtensorMap tmV,
            const __grid_constant__ CUtensorMap tmWo) {
  extern __shared__ __align__(1024) unsigned char smem_raw[];
  const uint32_t sbase = smem_u32(smem_raw);
  const uint32_t bar0 = sbase + BAR_OFF;
  auto full_bar = [&](int s) { return bar0 + s * 8; };
  auto empty_bar = [&](int s) { return bar0 + 72 + s * 8; };
  const uint32_t stash_bar = bar0 + 144, pro_bar = bar0 + 152, zgo_bar = bar0 + 160, zdone_bar = bar0 + 168;
  const int tid = threadIdx.x;
  if (blockIdx.x < NSIDE) { side_work(sa, smem_raw); return; }
  const int bid = blockIdx.x - NSIDE;
  const int qt = QT_OF(bid), grp = GRP_OF(bid);
  const int wg = __shfl_sync(0xffffffffu, tid >> 7, 0);
  unsigned char* const stash = g_stash + (size_t)bid * 6 * SLOT;
  uint2 xa[5], xb[5];
  uint4 wv[5];
  unsigned short cv[5];
  if (wg < 2) {
    const int row = qt * 128 + grp * 16 + (tid >> 5);
    if (bid < 80) {
      const bf16* wp = sa.w_mod + (size_t)(tid >> 1) * (6 * DM) + bid * 16 + (tid & 1) * 8;
#pragma unroll
      for (int i = 0; i < 5; i++) { wv[i] = __ldg((const uint4*)(wp + (size_t)i * 128 * 6 * DM)); cv[i] = __ldg((const unsigned short*)sa.c + (tid >> 1) + i * 128); }
    }
#pragma unroll
    for (int i = 0; i < 5; i++) {
      xa[i] = __ldg((const uint2*)(sa.x + (size_t)row * DM + i * 128) + (tid & 31));
      xb[i] = __ldg((const uint2*)(sa.x + (size_t)(row + 8) * DM + i * 128) + (tid & 31));
    }
  }
  if (tid == 288) { prefetch_tmap(&tmH); prefetch_tmap(&tmWq); prefetch_tmap(&tmK); prefetch_tmap(&tmV); prefetch_tmap(&tmWo); }
  if (tid == 256) {
    if (sbase & 1023) __trap();
    for (int s = 0; s < NSLOT; s++) { mbar_init(full_bar(s), 1); mbar_init(empty_bar(s), 8 * CLUSTER); }
    mbar_init(stash_bar, 8); mbar_init(pro_bar, 8); mbar_init(zgo_bar, 1); mbar_init(zdone_bar, 1);
    asm volatile("fence.mbarrier_init.release.cluster;" ::: "memory");
    fence_proxy_async_smem();
  }
  if (CLUSTER > 1) cluster_sync(); else __syncthreads();
  const int rank = blockIdx.x & 1;

  if (wg == 2) {
    asm volatile("setmaxnreg.dec.sync.aligned.u32 24;");
    if (tid == 256) {
      Pipe p{0, 1};
      auto acquire = [&](int bytes) {
        mbar_wait(empty_bar(p.slot), p.phase);
        mbar_expect_tx(full_bar(p.slot), bytes);
      };
      mbar_wait(pro_bar, 0);
#pragma unroll 1
      for (int kb = 0; kb < 4; kb++) {
        mbar_expect_tx(full_bar(2 * kb), 16384 + SLOT); mbar_arrive(full_bar(2 * kb + 1));
        ld_shared_3d((kb & 1) == rank, sbase + (2 * kb + 1) * SLOT, &tmWq, full_bar(2 * kb), 0, kb * 64, grp * 12);
      }
      tma_prefetch_3d(qt & 1 ? &tmV : &tmK, 0, grp * 4 * SEQ + (qt >> 1) * 64, 0);
      if (qt >= 4 && qt < 10) tma_prefetch_3d(&tmWq, 0, qt * 64, grp * 12);
      for (uint32_t it = 0; flag_ld(g_cnt2 + (16 + qt) * 32) < 8; it++)
        if (it > (1u << 22)) __trap();
#pragma unroll 1
      for (int kb = 0; kb < 4; kb++) tma_2d(sbase + 2 * kb * SLOT, &tmH, full_bar(2 * kb), kb * 64, qt * 128);
      p.slot = 8;
#pragma unroll 1
      for (int w = 0; w < 4; w++) {
        const int hd = grp * 4 + w;
#pragma unroll 1
        for (int kb = w == 0 ? 4 : 0; kb < 10; kb++) {
          const uint32_t fb = full_bar(p.slot);
          acquire(16384 + SLOT); tma_2d(sbase + p.slot * SLOT, &tmH, fb, kb * 64, QT_OF(fresh_ctaid()) * 128); p.next();
          mbar_wait(empty_bar(p.slot), p.phase); mbar_arrive(full_bar(p.slot));
          ld_shared_3d((kb & 1) == rank, sbase + p.slot * SLOT, &tmWq, fb, 0, kb * 64, hd * 3);
          p.next();
        }
        const int r0 = hd * SEQ;
        acquire(SLOT);
        ld_shared_3d(rank == 0, sbase + p.slot * SLOT, &tmK, full_bar(p.slot), 0, r0, 0);
        p.next();
#pragma unroll 1
        for (int j = 0; j < 31; j++) {
          const uint32_t fb = full_bar(p.slot);
          acquire(2 * SLOT);
          ld_shared_3d(rank == 0, sbase + p.slot * SLOT, &tmK, fb, 0, r0 + (j + 1) * 64, 0);
          p.next();
          mbar_wait(empty_bar(p.slot), p.phase); mbar_arrive(full_bar(p.slot));
          ld_shared_3d(rank == 1, sbase + p.slot * SLOT, &tmV, fb, 0, r0 + j * 64, 0);
          p.next();
          if (j == 4 || j == 8) {
            const int b = fresh_ctaid(), q = QT_OF(b), h0 = GRP_OF(b) * 4;
            if (w == 0 && j == 8) mbar_arrive(zgo_bar);
            if (j == 4) {
              if (w < 3) {
                if (q < 10) tma_prefetch_3d(&tmWq, 0, q * 64, (h0 + w + 1) * 3);
                else tma_prefetch_3d(q & 1 ? &tmV : &tmK, 0, (h0 + w + 1) * SEQ + ((q - 10) >> 1) * 64, 0);
              } else {
#pragma unroll 1
                for (int i = q; i < 40; i += 16) tma_prefetch_2d(&tmWo, (i >> 2) * 64, (h0 + (i & 3)) * DH);
              }
            } else if (w == 3) {
              mbar_wait(stash_bar, 0); fence_proxy_async_gmem();
#pragma unroll 1
              for (int k = 0; k < 2; k++) {
                int z;
                for (uint32_t it = 0;; it++) {
                  asm volatile("ld.acquire.gpu.global.s32 %0, [%1];" : "=r"(z) : "l"(g_cnt2 + (k ? 32 + q : 0) * 32) : "memory");
                  if (z >= (k ? 8 : NSIDE)) break;
                  if (it > (1u << 22)) __trap();
                }
              }
            }
          }
          if (w == 3 && j > 8 && j < 20) {
            const int b = fresh_ctaid(), k = j - 9;
            if (k < 6) l2_prefetch(g_stash + (size_t)(b * 6 + k) * SLOT, SLOT);
            else if (k < 8) l2_prefetch((k == 6 ? g_w1t : g_w2t) + b * 6400, 6400);
            else if (k < 10) l2_prefetch((k == 8 ? g_w4t : (const unsigned char*)sa.w3) + b * 15360, 15360);
            else {
              l2_prefetch((const unsigned char*)sa.x + b * 20480, 20480);
              if (b == 0) { l2_prefetch(g_modp, DM * 8); l2_prefetch(g_cs3, FF * 4); }
            }
          }
        }
        acquire(SLOT);
        ld_shared_3d(rank == 1, sbase + p.slot * SLOT, &tmV, full_bar(p.slot), 0, r0 + 31 * 64, 0);
        p.next();
      }
#pragma unroll 1
      for (int s = 0; s < FIN_PIN; s++) {
        acquire(SLOT);
        bulk_g2s(sbase + p.slot * SLOT, g_stash + (size_t)(fresh_ctaid() * 6 + s) * SLOT, SLOT, full_bar(p.slot));
        p.next();
      }
      int ri = 0; uint32_t rph = 1;
#pragma unroll 1
      for (int i = 0; i < 40; i++) {
        const int s = fin_slot(FIN_PIN + ri);
        mbar_wait(empty_bar(s), fin_round(FIN_PIN + ri) ^ rph);
        mbar_expect_tx(full_bar(s), SLOT);
        const int g = GRP_OF(fresh_ctaid());
        ld_shared_2d((i & 1) == rank, sbase + s * SLOT, &tmWo, full_bar(s), (((i >> 2) + g) % 10) * 64, (g * 4 + ((i + 3) & 3)) * DH);
        if (++ri == FIN_RING) { ri = 0; rph ^= 1; }
        if (i == 30) { __threadfence(); pdl_trigger(); }
      }
    } else if (tid >= 288 && tid < 320) {
      mbar_wait(zgo_bar, 0);
#pragma unroll 1
      for (int i = tid - 288; i < 512; i += 32) ((uint4*)(smem_raw + STAGE_OFF))[i] = make_uint4(0, 0, 0, 0);
      fence_proxy_async_smem();
      __syncwarp();
      if (tid == 288) {
#pragma unroll 1
        for (int i = 0; i < 5; i++) bulk_s2g((unsigned char*)g_acc + (size_t)((qt * 8 + grp) * 5 + i) * 8192, sbase + STAGE_OFF, 8192);
        bulk_commit();
        bulk_wait<0>();
        mbar_arrive(zdone_bar);
        flag_add(g_cnt2 + (32 + qt) * 32);
      }
    }
    __syncwarp();
    if (CLUSTER > 1) cluster_sync();
  } else {
    asm volatile("setmaxnreg.inc.sync.aligned.u32 240;");
    const int warp4 = (tid >> 5) & 3, lane = tid & 31;
    const float cs = 0.07216878364870322f * 1.4426950408889634f;
    float o[96], s[32];
    uint32_t q[48], pa[16], pb[16];
    Pipe p{0, 0};
    uint4* const stash2 = (uint4*)(stash + 4 * SLOT) + tid;
    const uint32_t ebase = CLUSTER > 1 ? mapa(empty_bar(0), lane & 1) : empty_bar(0);
    auto release = [&](int slot) {
      if (CLUSTER > 1) { if (lane < 2) mbar_arrive_cluster(ebase + slot * 8); }
      else { if (lane == 0) mbar_arrive(ebase + slot * 8); }
    };
    if (wg == 1) bar_arrive(1, 256);

    {
      const int warp = tid >> 5, b = bid;
      uint32_t* smod = (uint32_t*)(smem_raw + STAGE_OFF);
      float* part = (float*)(smem_raw + STAGE_OFF + 5120);
      if (b < 80) {
        float a[8];
#pragma unroll
        for (int j = 0; j < 8; j++) a[j] = 0.f;
#pragma unroll
        for (int i = 0; i < 5; i++) {
          const float f = silu_bf16(__ushort_as_bfloat16(cv[i]));
          a[0] = fmaf(f, bf_lo(wv[i].x), a[0]); a[1] = fmaf(f, bf_hi(wv[i].x), a[1]); a[2] = fmaf(f, bf_lo(wv[i].y), a[2]); a[3] = fmaf(f, bf_hi(wv[i].y), a[3]);
          a[4] = fmaf(f, bf_lo(wv[i].z), a[4]); a[5] = fmaf(f, bf_hi(wv[i].z), a[5]); a[6] = fmaf(f, bf_lo(wv[i].w), a[6]); a[7] = fmaf(f, bf_hi(wv[i].w), a[7]);
        }
#pragma unroll
        for (int o2 = 2; o2 <= 16; o2 <<= 1)
#pragma unroll
          for (int j = 0; j < 8; j++) a[j] += __shfl_xor_sync(0xffffffffu, a[j], o2);
        if (lane < 2)
#pragma unroll
          for (int j = 0; j < 8; j++) part[warp * 16 + lane * 8 + j] = a[j];
        bar_sync(3, 256);
        if (tid < 16) {
          float t = 0.f;
#pragma unroll
          for (int r = 0; r < 8; r++) t += part[r * 16 + tid];
          t = bf16r(t);
          if (b >= 40) t = bf16r(1.0f + t);
          const uint32_t word = __float_as_uint(t) | 1u;
          asm volatile("st.relaxed.gpu.global.u32 [%0], %1;" ::"l"(g_modc + b * 16 + tid), "r"(word) : "memory");
        }
      }
      float va[20], vb[20];
#pragma unroll
      for (int i = 0; i < 5; i++) {
        va[i * 4] = bf_lo(xa[i].x); va[i * 4 + 1] = bf_hi(xa[i].x); va[i * 4 + 2] = bf_lo(xa[i].y); va[i * 4 + 3] = bf_hi(xa[i].y);
        vb[i * 4] = bf_lo(xb[i].x); vb[i * 4 + 1] = bf_hi(xb[i].x); vb[i * 4 + 2] = bf_lo(xb[i].y); vb[i * 4 + 3] = bf_hi(xb[i].y);
      }
      float ta = 0.f, tb = 0.f;
#pragma unroll
      for (int i = 0; i < 20; i++) { ta += va[i]; tb += vb[i]; }
#pragma unroll
      for (int o2 = 16; o2 > 0; o2 >>= 1) { ta += __shfl_xor_sync(0xffffffffu, ta, o2); tb += __shfl_xor_sync(0xffffffffu, tb, o2); }
      const float ma = ta * (1.0f / DM), mb = tb * (1.0f / DM);
      if (lane == 0 && ma == ma) mbar_arrive(pro_bar); else if (lane == 0) mbar_arrive(pro_bar);
      ta = 0.f; tb = 0.f;
#pragma unroll
      for (int i = 0; i < 20; i++) { va[i] -= ma; vb[i] -= mb; ta = fmaf(va[i], va[i], ta); tb = fmaf(vb[i], vb[i], tb); }
#pragma unroll
      for (int o2 = 16; o2 > 0; o2 >>= 1) { ta += __shfl_xor_sync(0xffffffffu, ta, o2); tb += __shfl_xor_sync(0xffffffffu, tb, o2); }
      const float ra = rsqrtf(ta * (1.0f / DM) + 1e-5f), rb = rsqrtf(tb * (1.0f / DM) + 1e-5f);
#pragma unroll
      for (int i = 0; i < 20; i++) { va[i] *= ra; vb[i] *= rb; }
      fence_regs(va); fence_regs(vb);
      if (tid < 160) {
        uint4 m, m2;
        for (uint32_t it = 0;; it++) {
          asm volatile("ld.relaxed.gpu.global.v4.u32 {%0, %1, %2, %3}, [%4];" : "=r"(m.x), "=r"(m.y), "=r"(m.z), "=r"(m.w) : "l"(g_modc + tid * 4) : "memory");
          asm volatile("ld.relaxed.gpu.global.v4.u32 {%0, %1, %2, %3}, [%4];" : "=r"(m2.x), "=r"(m2.y), "=r"(m2.z), "=r"(m2.w) : "l"(g_modc + DM + tid * 4) : "memory");
          if (m.x & m.y & m.z & m.w & m2.x & m2.y & m2.z & m2.w & 1u) break;
          if (it > (1u << 22)) __trap();
        }
        *(uint4*)(smod + tid * 4) = make_uint4(m.x ^ 1u, m.y ^ 1u, m.z ^ 1u, m.w ^ 1u);
        *(uint4*)(smod + DM + tid * 4) = make_uint4(m2.x ^ 1u, m2.y ^ 1u, m2.z ^ 1u, m2.w ^ 1u);
      }
      bar_sync(3, 256);
      uint2* hs = (uint2*)(smem_raw + 8 * SLOT) + warp * 160 + lane;
#pragma unroll
      for (int i = 0; i < 5; i++) {
        const float4 s4 = *(const float4*)(smod + i * 128 + lane * 4), c4 = *(const float4*)(smod + DM + i * 128 + lane * 4);
        hs[i * 32] = make_uint2(pack_bf16(fmaf(va[i * 4], c4.x, s4.x), fmaf(va[i * 4 + 1], c4.y, s4.y)),
                                pack_bf16(fmaf(va[i * 4 + 2], c4.z, s4.z), fmaf(va[i * 4 + 3], c4.w, s4.w)));
        hs[1280 + i * 32] = make_uint2(pack_bf16(fmaf(vb[i * 4], c4.x, s4.x), fmaf(vb[i * 4 + 1], c4.y, s4.y)),
                                       pack_bf16(fmaf(vb[i * 4 + 2], c4.z, s4.z), fmaf(vb[i * 4 + 3], c4.w, s4.w)));
      }
      fence_proxy_async_smem();
      bar_sync(3, 256);
      if (tid == 0) {
        bulk_s2g(g_h + (size_t)(qt * 128 + grp * 16) * DM, sbase + 8 * SLOT, 20480);
        bulk_commit();
        bulk_wait<0>();
        flag_add(g_cnt2 + (16 + qt) * 32);
      }
      __syncwarp();
    }

#pragma unroll 1
    for (int w = 0; w < 4; w++) {
      int prevH = 0, prevW = 0;
#pragma unroll
      for (int kb = 0; kb < 10; kb++) {
        const int sH = p.slot; mbar_wait(full_bar(sH), p.phase); p.next();
        const int sW = p.slot; p.next();
        const uint32_t dA = mkdesc(sbase + sH * SLOT + wg * 8192, 16);
        const uint32_t dB = mkdesc(sbase + sW * SLOT, 8192);
        if (kb == 9) bar_sync(1 + wg, 256);
        wg_fence();
#pragma unroll
        for (int kk = 0; kk < 4; kk++) wgmma_m64n192k16_ss_tb1(o, dA + kk * 2, dB + kk * 128, (kb | kk) != 0);
        wg_commit();
        if (kb == 9) bar_arrive(1 + (wg ^ 1), 256);
        if (kb >= 1 && kb <= 6) {
          const int u = kb - 1, blk = u >> 1, hf = u & 1;
          if (w == 1 || w == 2) {
            if (kb == 1) mbar_wait(zdone_bar, 0);
            if (lane == 0) bulk_wait_read<0>();
            __syncwarp();
            const uint32_t stg = sbase + STAGE_OFF + (tid >> 5) * 1024;
            const int r = lane & 7, m = lane >> 3;
#pragma unroll
            for (int t = 0; t < 2; t++) {
              const int k0 = blk * 4 + t * 2;
              stmatrix_x4(stg + r * 128 + (((t * 4 + m) ^ r) << 4), q[k0 * 4 + hf], q[k0 * 4 + 2 + hf], q[k0 * 4 + 4 + hf], q[k0 * 4 + 6 + hf]);
            }
            fence_proxy_async_smem();
            __syncwarp();
            if (lane == 0) {
              bulk_s2g(stash + ((w - 1) * 2 + wg) * SLOT + blk * 8192 + (warp4 * 16 + hf * 8) * 128, stg, 1024);
              bulk_commit();
            }
          } else if (w == 3) {
#pragma unroll
            for (int kk = 2 * u; kk < 2 * u + 2; kk++) stash2[kk * 256] = make_uint4(q[kk * 4], q[kk * 4 + 1], q[kk * 4 + 2], q[kk * 4 + 3]);
          }
        }
        if (kb == 0 && w == 3 && lane == 0) { bulk_wait<0>(); mbar_arrive(stash_bar); }
        if (kb < 5) {
          wg_wait<0>();
          release(sH); release(sW);
        } else {
          wg_wait<1>();
          if (kb > 5) { release(prevH); release(prevW); }
        }
        prevH = sH; prevW = sW;
      }
      wg_wait<0>();
      fence_regs(o);
      release(prevH); release(prevW);
#pragma unroll
      for (int i = 0; i < 48; i++) q[i] = pack_bf16(o[2 * i], o[2 * i + 1]);

      float m0 = -INFINITY, m1 = -INFINITY, l0 = 0.f, l1 = 0.f, sc0, sc1;
      bool upd;
      const float RESCALE_T = 8.0f / cs;
      auto issue_qk = [&](int slot) {
        const uint32_t dK = mkdesc(sbase + slot * SLOT, 16);
#pragma unroll
        for (int kk = 0; kk < 12; kk++)
          wgmma_m64n64k16_rs_tb0(s, q[kk * 4], q[kk * 4 + 1], q[kk * 4 + 2], q[kk * 4 + 3], dK + (kk >> 2) * 512 + (kk & 3) * 2, kk != 0);
        wg_commit();
      };
      int keep = 0;
      auto issue_pv = [&](int slot, uint32_t (&pf)[16]) {
        const uint32_t dV = mkdesc(sbase + slot * SLOT, 8192);
#pragma unroll
        for (int kk = 0; kk < 4; kk++)
          wgmma_m64n192k16_rs_tb1(o, pf[kk * 4], pf[kk * 4 + 1], pf[kk * 4 + 2], pf[kk * 4 + 3], dV + kk * 128, kk == 0 ? keep : 1);
        keep = 1;
        wg_commit();
      };
      auto softmax = [&](uint32_t (&pf)[16]) {
        float a0 = fmaxf(s[0], s[1]), a1 = fmaxf(s[2], s[3]), a2 = fmaxf(s[4], s[5]), a3 = fmaxf(s[6], s[7]);
#pragma unroll
        for (int j = 2; j < 8; j += 2) {
          a0 = fmaxf(a0, fmaxf(s[4 * j], s[4 * j + 1]));
          a1 = fmaxf(a1, fmaxf(s[4 * j + 2], s[4 * j + 3]));
          a2 = fmaxf(a2, fmaxf(s[4 * j + 4], s[4 * j + 5]));
          a3 = fmaxf(a3, fmaxf(s[4 * j + 6], s[4 * j + 7]));
        }
        a0 = fmaxf(a0, a2); a1 = fmaxf(a1, a3);
        a0 = fmaxf(a0, __shfl_xor_sync(0xffffffffu, a0, 1)); a1 = fmaxf(a1, __shfl_xor_sync(0xffffffffu, a1, 1));
        a0 = fmaxf(a0, __shfl_xor_sync(0xffffffffu, a0, 2)); a1 = fmaxf(a1, __shfl_xor_sync(0xffffffffu, a1, 2));
        const bool u0 = a0 > m0 + RESCALE_T, u1 = a1 > m1 + RESCALE_T;
        a0 = u0 ? a0 : m0; a1 = u1 ? a1 : m1;
        const float b0 = -a0 * cs, b1 = -a1 * cs;
        sc0 = ex2(fmaf(m0, cs, b0)); sc1 = ex2(fmaf(m1, cs, b1));
        m0 = a0; m1 = a1;
        upd = __any_sync(0xffffffffu, u0 || u1);
        float r0 = 0.f, r1 = 0.f, r2 = 0.f, r3 = 0.f;
#pragma unroll
        for (int j = 0; j < 8; j++) {
          const float e0 = ex2(fmaf(s[4 * j], cs, b0)), e1 = ex2(fmaf(s[4 * j + 1], cs, b0));
          const float e2 = ex2(fmaf(s[4 * j + 2], cs, b1)), e3 = ex2(fmaf(s[4 * j + 3], cs, b1));
          r0 += e0; r2 += e1; r1 += e2; r3 += e3;
          pf[2 * j] = pack_bf16(e0, e1); pf[2 * j + 1] = pack_bf16(e2, e3);
        }
        l0 = fmaf(l0, sc0, r0 + r2); l1 = fmaf(l1, sc1, r1 + r3);
      };
      auto rescale = [&]() {
#pragma unroll
        for (int j = 0; j < 24; j++) { o[4 * j] *= sc0; o[4 * j + 1] *= sc0; o[4 * j + 2] *= sc1; o[4 * j + 3] *= sc1; }
      };
      auto step = [&](uint32_t (&pcur)[16], uint32_t (&pnxt)[16]) {
        const int sK = p.slot; p.next();
        const int sV = p.slot; p.next();
        bar_sync(1 + wg, 256);
        wg_fence();
        issue_qk(sK);
        issue_pv(sV, pcur);
        bar_arrive(1 + (wg ^ 1), 256);
        const bool ready = mbar_test(full_bar(p.slot), p.phase);
        wg_wait<1>();
        fence_regs(s);
        release(sK);
        softmax(pnxt);
        if (!ready) mbar_wait(full_bar(p.slot), p.phase);
        wg_wait<0>();
        fence_regs(o);
        fence_regs_u(pcur);
        release(sV);
        if (upd) rescale();
      };

      {
        const int sK = p.slot; mbar_wait(full_bar(sK), p.phase); p.next();
        bar_sync(1 + wg, 256);
        wg_fence();
        issue_qk(sK);
        bar_arrive(1 + (wg ^ 1), 256);
        const bool ready = mbar_test(full_bar(p.slot), p.phase);
        wg_wait<0>();
        fence_regs(s);
        release(sK);
        softmax(pa);
        if (!ready) mbar_wait(full_bar(p.slot), p.phase);
      }
#pragma unroll 1
      for (int j = 0; j < 15; j++) {
        step(pa, pb); step(pb, pa);
      }
      step(pa, pb);
      {
        const int sV = p.slot; p.next();
        wg_fence();
        issue_pv(sV, pb);
        wg_wait<0>();
        fence_regs(o);
        release(sV);
      }
      l0 += __shfl_xor_sync(0xffffffffu, l0, 1); l1 += __shfl_xor_sync(0xffffffffu, l1, 1);
      l0 += __shfl_xor_sync(0xffffffffu, l0, 2); l1 += __shfl_xor_sync(0xffffffffu, l1, 2);
      const float i0 = __frcp_rn(l0), i1 = __frcp_rn(l1);
#pragma unroll
      for (int j = 0; j < 24; j++) {
        q[2 * j] = pack_bf16(o[4 * j] * i0, o[4 * j + 1] * i0);
        q[2 * j + 1] = pack_bf16(o[4 * j + 2] * i1, o[4 * j + 3] * i1);
      }
    }

    uint32_t q2[48];
#pragma unroll
    for (int kk = 0; kk < 12; kk++) {
      const uint4 v = stash2[kk * 256];
      q2[kk * 4] = v.x; q2[kk * 4 + 1] = v.y; q2[kk * 4 + 2] = v.z; q2[kk * 4 + 3] = v.w;
    }
    float* accp = g_acc + (size_t)((qt * 2 + wg) * 4 + warp4) * 10240 + lane * 4;
    float accA[32], accB[32];
    const uint32_t dA0 = mkdesc(sbase + fin_slot(wg) * SLOT, 16), dA1 = mkdesc(sbase + fin_slot(2 + wg) * SLOT, 16);
    int prev = -1, ri = 0;
    uint32_t rph = 0;
    auto chunk = [&](int c, float (&acc)[32], float (&old)[32]) {
#pragma unroll
      for (int h = 0; h < 4; h++) {
        const int sl = fin_slot(FIN_PIN + ri);
        mbar_wait(full_bar(sl), fin_round(FIN_PIN + ri) ^ rph);
        if (++ri == FIN_RING) { ri = 0; rph ^= 1; }
        if (c == 0 && (h == 1 || h == 2)) mbar_wait(full_bar(fin_slot((h - 1) * 2 + wg)), fin_round((h - 1) * 2 + wg));
        const uint32_t dB = mkdesc(sbase + sl * SLOT, 8192);
        wg_fence();
        if (h == 0) {
#pragma unroll
          for (int kk = 0; kk < 12; kk++) wgmma_m64n64k16_rs_tb1(acc, q[kk * 4], q[kk * 4 + 1], q[kk * 4 + 2], q[kk * 4 + 3], dB + kk * 128, kk != 0);
        } else if (h < 3) {
          const uint32_t dA = h == 1 ? dA0 : dA1;
#pragma unroll
          for (int kk = 0; kk < 12; kk++) wgmma_m64n64k16_ss_tb1(acc, dA + (kk >> 2) * 512 + (kk & 3) * 2, dB + kk * 128, 1);
        } else {
#pragma unroll
          for (int kk = 0; kk < 12; kk++) wgmma_m64n64k16_rs_tb1(acc, q2[kk * 4], q2[kk * 4 + 1], q2[kk * 4 + 2], q2[kk * 4 + 3], dB + kk * 128, 1);
        }
        wg_commit();
        wg_wait<1>();
        if (prev >= 0) release(prev);
        prev = sl;
        if (c > 0) {
          if (h == 0) fence_regs(old);
#pragma unroll
          for (int j = 2 * h; j < 2 * h + 2; j++)
            red_add_v4(accp + ((c - 1 + grp) % 10) * 1024 + j * 128, old[4 * j], old[4 * j + 1], old[4 * j + 2], old[4 * j + 3]);
        }
      }
    };
#pragma unroll 1
    for (int c = 0; c < 10; c += 2) {
      chunk(c, accA, accB);
      chunk(c + 1, accB, accA);
      wg_wait<0>();
      fence_regs(accB);
    }
    fence_regs(accB);
#pragma unroll
    for (int j = 0; j < 8; j++) red_add_v4(accp + ((9 + grp) % 10) * 1024 + j * 128, accB[4 * j], accB[4 * j + 1], accB[4 * j + 2], accB[4 * j + 3]);
    __threadfence();
    __syncwarp();
    if (lane == 0) flag_add(g_cnt3 + qt * 32);
    if (CLUSTER > 1) cluster_sync();
  }
}

constexpr int PA_N = 6, PA_SZ = 16384, PB_N = 5, PB_SZ = 24576;
static_assert(PA_N == 6, "start-up staging layout / G4 must start at ring slot 0");
constexpr int PB_OFF = PA_N * PA_SZ;
constexpr int PBAR_OFF = PB_OFF + PB_N * PB_SZ;
constexpr int ACC_STG = 40960, XT0 = 24576, XT1 = 81920;
constexpr int STAT_OFF = PBAR_OFF + 512 + 768 + 5120;
constexpr int POST_SMEM = STAT_OFF + 1024;

__device__ __forceinline__ void tma_store_2d(const CUtensorMap* tm, uint32_t src, int c0, int c1) {
  asm volatile("cp.async.bulk.tensor.2d.global.shared::cta.bulk_group [%0, {%2, %3}], [%1];" ::"l"(tm), "r"(src), "r"(c0), "r"(c1) : "memory");
}
template <int N> struct Ring {
  int slot; uint32_t phase;
  __device__ __forceinline__ void next() { if (++slot == N) { slot = 0; phase ^= 1; } }
};
__device__ __forceinline__ uint32_t bf2_mul(uint32_t a, uint32_t b) { uint32_t r; asm("mul.rn.bf16x2 %0, %1, %2;" : "=r"(r) : "r"(a), "r"(b)); return r; }
__device__ __forceinline__ uint32_t bf2_add(uint32_t a, uint32_t b) { uint32_t r; asm("add.rn.bf16x2 %0, %1, %2;" : "=r"(r) : "r"(a), "r"(b)); return r; }
__device__ __forceinline__ float4 ln_stats2(const uint32_t (&a)[10], const uint32_t (&b)[10]) {
  float sa = 0.f, qa = 0.f, sb = 0.f, qb = 0.f;
#pragma unroll
  for (int i = 0; i < 10; i++) {
    const float a0 = bf_lo(a[i]), a1 = bf_hi(a[i]), b0 = bf_lo(b[i]), b1 = bf_hi(b[i]);
    sa += a0 + a1; qa = fmaf(a0, a0, qa); qa = fmaf(a1, a1, qa);
    sb += b0 + b1; qb = fmaf(b0, b0, qb); qb = fmaf(b1, b1, qb);
  }
#pragma unroll
  for (int o = 16; o > 0; o >>= 1) {
    sa += __shfl_xor_sync(0xffffffffu, sa, o); qa += __shfl_xor_sync(0xffffffffu, qa, o);
    sb += __shfl_xor_sync(0xffffffffu, sb, o); qb += __shfl_xor_sync(0xffffffffu, qb, o);
  }
  const float ma = sa * (1.0f / DM), mb = sb * (1.0f / DM);
  const float ra = rsqrtf(fmaxf(qa * (1.0f / DM) - ma * ma, 0.f) + 1e-5f), rb = rsqrtf(fmaxf(qb * (1.0f / DM) - mb * mb, 0.f) + 1e-5f);
  return make_float4(ra, -ma * ra, rb, -mb * rb);
}

struct PostMaps { CUtensorMap aT, aG, aX1, lX, bW3, sG, sX1, sOut; };

__global__ void __cluster_dims__(2, 1, 1) __launch_bounds__(384, 1)
post_kernel(const bf16* __restrict__ x, const __grid_constant__ PostMaps tm) {
  extern __shared__ __align__(1024) unsigned char smem_raw[];
  const uint32_t sbase = smem_u32(smem_raw);
  const uint32_t bar0 = sbase + PBAR_OFF;
  auto fullA = [&](int s, int h) { return bar0 + (s * 2 + h) * 8; };
  auto emptyA = [&](int s) { return bar0 + 96 + s * 8; };
  auto empty4 = [&](int s, int h) { return bar0 + 144 + (s * 2 + h) * 8; };
  auto fullB = [&](int s) { return bar0 + 240 + s * 8; };
  auto emptyB = [&](int s) { return bar0 + 280 + s * 8; };
  auto stgbar = [&](int w, int ev) { return bar0 + 320 + (w * 8 + ev) * 8; };
  const uint32_t accbar = bar0 + 448, xbar = bar0 + 456, tabbar = bar0 + 496;
  auto xfree = [&](int w) { return bar0 + 464 + w * 8; };
  auto xfull = [&](int w) { return bar0 + 480 + w * 8; };
  float* const sv = (float*)(smem_raw + PBAR_OFF + 512);
  const uint4* const tab = (const uint4*)(sv + 192);
  const int tid = threadIdx.x;
  const int R = blockIdx.x >> 3, n = blockIdx.x & 7, rank = blockIdx.x & 1;
  const int wg = __shfl_sync(0xffffffffu, tid >> 7, 0);
  const int warp = __shfl_sync(0xffffffffu, tid >> 5, 0), lane = tid & 31;
  uint32_t xa[10], xb[10];
  if (wg < 2) {
    const int ra = R * 128 + n * 16 + warp;
#pragma unroll
    for (int i = 0; i < 10; i++) {
      xa[i] = __ldg((const uint32_t*)(x + (size_t)ra * DM + i * 64) + lane);
      xb[i] = __ldg((const uint32_t*)(x + (size_t)(ra + 8) * DM + i * 64) + lane);
    }
  }
  if (tid == 256) {
    if (sbase & 1023) __trap();
    for (int s = 0; s < 12; s++) { mbar_init(fullA(0, s), 1); mbar_init(empty4(0, s), s < 6 ? 5 : 4); }
    for (int s = 0; s < 16; s++) mbar_init(stgbar(0, s), 4);
    for (int s = 0; s < PA_N; s++) mbar_init(emptyA(s), 8);
    for (int s = 0; s < PB_N; s++) { mbar_init(fullB(s), 1); mbar_init(emptyB(s), 8); }
    mbar_init(xfree(0), 4); mbar_init(xfree(1), 4); mbar_init(xfull(0), 1); mbar_init(xfull(1), 1);
    for (int s = 0; s < 12; s++) mbar_expect_tx(fullA(0, s), 8192);
    mbar_expect_tx(xfull(0), 20480); mbar_expect_tx(xfull(1), 20480);
    asm volatile("fence.mbarrier_init.release.cluster;" ::: "memory");
    fence_proxy_async_smem();
  }
  if (tid == 288) {
    mbar_init(accbar, 1); mbar_init(xbar, 1); mbar_init(tabbar, 1);
    asm volatile("fence.mbarrier_init.release.cluster;" ::: "memory");
    fence_proxy_async_smem();
    fence_proxy_async_gmem();
    mbar_expect_tx(tabbar, 768 + 5120);
    bulk_g2s(sbase + PBAR_OFF + 512 + 768, g_modp, 5120, tabbar);
    bulk_g2s(sbase + PBAR_OFF + 512, g_cs3 + n * 192, 768, tabbar);
  }
  if (tid >= 320 && tid < 328) prefetch_tmap(&tm.aT + (tid - 320));
  __syncwarp();
  asm volatile("barrier.cluster.arrive.relaxed.aligned;" ::: "memory");
  if (tid == 288) {
    for (uint32_t it = 0;; it++) {
      int z;
      asm volatile("ld.acquire.gpu.global.s32 %0, [%1];" : "=r"(z) : "l"(g_cnt3 + R * 32) : "memory");
      if (z >= 64) break;
      if (it > (1u << 22)) __trap();
    }
    fence_proxy_async_gmem();
    mbar_expect_tx(accbar, 40960);
    bulk_g2s(sbase + ACC_STG, g_acc + (size_t)(R * 8 + n) * 10240, 40960, accbar);
    mbar_expect_tx(xbar, 20480);
#pragma unroll 1
    for (int i = 0; i < 4; i++) tma_2d(sbase + (i < 2 ? XT0 : XT1) + (i & 1) * 5120, &tm.lX, xbar, n * 80, R * 128 + i * 32);
  }
  __syncwarp();
  asm volatile("barrier.cluster.wait.aligned;" ::: "memory");
  const int r64 = R * 2;

  if (wg == 2) {
    asm volatile("setmaxnreg.dec.sync.aligned.u32 72;");
    if (warp == 8) {
      Ring<PA_N> p{0, 1};
      const int my = r64 + rank;
      const int fblk = lane < 8 ? my : lane < 16 ? (my ^ 1) : lane < 24 ? my - 1 : my + 1;
      const bool fvalid = fblk >= 0 && fblk < 32;
#pragma unroll 1
      for (int st = 0; st < 3; st++) {
        const CUtensorMap* m = &tm.aT + st;
        const int* fp = g_flag + (st * 32 + (fvalid ? fblk : my)) * 8 + (lane & 7);
        uint32_t need;
        if (st == 0) need = 0x0fu | ((3u << (n & 2)) << ((n >> 2) == rank ? 0 : 8));
        else {
          const int s0 = (lane * 64) / 80, s1 = (lane * 64 + 63) / 80;
          need = lane < 10 ? (1u << s0) | (1u << s1) : 0u;
          if (st == 1) {
            if (my > 0) need |= (need & 0x33u) << 16;
            if (my < 31) need |= (need & 0xccu) << 24;
          }
          if (lane == 0) need |= 3u << (n & 6);
        }
        const uint32_t need2 = st == 2 && lane == 9 ? 0xffu : 0u;
        int cur = 0;
        uint32_t rdy = 0;
        for (uint32_t it = 0; cur < 10; it++) {
          if ((rdy & 0x3ffu) != 0x3ffu) {
            const int v = flag_ld(fp);
            const uint32_t have = __ballot_sync(0xffffffffu, v >= 1), have2 = __ballot_sync(0xffffffffu, v >= 2);
            rdy = __ballot_sync(0xffffffffu, (have & need) == need && (have2 & need2) == need2);
          }
          const int i = cur + lane, pos = p.slot + lane;
          const int slot = pos >= PA_N ? pos - PA_N : pos;
          const uint32_t ph = p.phase ^ (pos >= PA_N ? 1u : 0u);
          const bool ok = lane < PA_N && i < 10 && ((rdy >> i) & 1u) && mbar_test(emptyA(slot), ph);
          const int cnt = __ffs(~__ballot_sync(0xffffffffu, ok)) - 1;
          if (lane < cnt) tma_2d_mc(sbase + slot * PA_SZ + rank * 8192, m, fullA(slot, rank), i * 64, R * 128 + rank * 64);
          __syncwarp();
          p.slot += cnt;
          if (p.slot >= PA_N) { p.slot -= PA_N; p.phase ^= 1; }
          cur += cnt;
          if (it > (1u << 24)) __trap();
        }
      }
      {
        const int h = lane >> 4, j = lane & 15;
        const int* fp = g_flag + (3 * 32 + r64 + h) * 8 + (lane & 7);
        const int bq = j / 3, sl = (n + 2 * (j % 3 + 1)) & 7, slot = (j + 3) % 6;
        int cur = 0;
        uint32_t rdy = 0;
        for (uint32_t it = 0;; it++) {
          if (rdy != 0x01ff01ffu) {
            const int v = flag_ld(fp);
            const uint32_t h1 = __ballot_sync(0xffffffffu, v >= 1), h2 = __ballot_sync(0xffffffffu, v >= 2), h3 = __ballot_sync(0xffffffffu, v >= 3);
            rdy = __ballot_sync(0xffffffffu, j < 9 && (((bq == 0 ? h1 : bq == 1 ? h2 : h3) >> (h * 16 + sl)) & 1u));
          }
          const bool ok = j >= cur && j < 9 && j < cur + 6 && ((rdy >> lane) & 1u) && mbar_test(empty4(slot, h), j >= 6);
          const int cnt = __ffs(~(((__ballot_sync(0xffffffffu, ok) >> (h * 16)) & 0xffffu) >> cur)) - 1;
          if (j >= cur && j < cur + cnt)
            bulk_g2s(sbase + slot * PA_SZ + h * 8192, (const unsigned char*)g_h2 + (size_t)(R * 24 + sl * 3 + bq) * PA_SZ + h * 8192, 8192, fullA(slot, h));
          __syncwarp();
          cur += cnt;
          if (__all_sync(0xffffffffu, cur >= 9)) break;
          if (it > (1u << 24)) __trap();
        }
      }
    } else if (tid == 288) {
      Ring<PB_N> p{0, 1};
      mbar_wait(accbar, 0);
#pragma unroll 1
      for (int i = 0; i < 32; i++) {
        mbar_wait(emptyB(p.slot), p.phase);
        const uint32_t dst = sbase + PB_OFF + p.slot * PB_SZ;
        if (i < 10) {
          mbar_expect_tx(fullB(p.slot), 20480);
          bulk_g2s(dst, (i < 5 ? g_w1t : g_w2t) + (size_t)(n * 5 + (i < 5 ? i : i - 5)) * 20480, 20480, fullB(p.slot));
        } else if (i < 20) {
          mbar_expect_tx(fullB(p.slot), PB_SZ);
          tma_3d(dst, &tm.bW3, fullB(p.slot), 0, (i - 10) * 64, n * 3);
        } else {
          mbar_expect_tx(fullB(p.slot), 20480);
          const int j = i - 23;
          const int kb = j < 0 ? n * 3 + j + 3 : ((n + 2 * (j % 3 + 1)) & 7) * 3 + j / 3;
          bulk_g2s(dst, g_w4t + (size_t)((n & 6) * 24 + kb) * 10240, 10240, fullB(p.slot));
          bulk_g2s(dst + 10240, g_w4t + (size_t)((n | 1) * 24 + kb) * 10240, 10240, fullB(p.slot));
        }
        p.next();
      }
      pdl_wait();
    } else if (tid == 320 || tid == 352) {
      const int w = warp - 10;
      const uint32_t stg = sbase + w * 8192;
      const int row = R * 128 + w * 64;
      int* fl = g_flag + (32 + r64 + w) * 8 + n;
      const int g4 = n >> 1, sh = g4 == 0 ? 3 : g4 == 1 ? 1 : g4 == 2 ? 4 : 0;
      mbar_wait(stgbar(w, 0), 0);
      tma_store_2d(&tm.sG, stg, n * 80, row + sh); tma_store_2d(&tm.sG, stg + PA_SZ, n * 80, row + 32 + sh);
      bulk_commit(); bulk_wait<0>(); flag_add(fl);
      mbar_wait(stgbar(w, 1), 0);
      tma_store_2d(&tm.sX1, stg, n * 80, row); tma_store_2d(&tm.sX1, stg + PA_SZ, n * 80, row + 32);
      bulk_commit();
      mbar_wait(stgbar(w, 6), 0);
      bulk_s2g(g_stats + ((size_t)n * SEQ + row) * 2, sbase + STAT_OFF + w * 512, 512);
      bulk_commit();
      bulk_wait<1>(); flag_add(fl + 256);
      bulk_wait<0>(); flag_add(fl + 256);
#pragma unroll 1
      for (int bq = 0; bq < 3; bq++) {
        mbar_wait(stgbar(w, 2 + bq), 0);
        bulk_s2g((unsigned char*)g_h2 + (size_t)(R * 24 + n * 3 + bq) * PA_SZ + w * 8192, stg + bq * PA_SZ, 8192);
        bulk_commit();
        if (bq > 0) { bulk_wait<1>(); flag_add(fl + 512); }
      }
      bulk_wait<0>(); flag_add(fl + 512);
      for (int k = 0; k < 3; k++) mbar_arrive(empty4(k, w));
      mbar_wait(stgbar(w, 5), 0);
      tma_store_2d(&tm.sOut, stg + 3 * PA_SZ, n * 80, row); tma_store_2d(&tm.sOut, stg + 4 * PA_SZ, n * 80, row + 32);
      bulk_commit(); bulk_wait_read<0>();
    }
    __syncwarp();
    cluster_sync();
  } else {
    asm volatile("setmaxnreg.inc.sync.aligned.u32 216;");
    const int warp4 = warp & 3;
    const int row0 = R * 128 + wg * 64 + warp4 * 16 + (lane >> 2);
    const uint4* const svp = tab + n * 40;
    uint32_t x2r[20];
    {
      mbar_wait(tabbar, 0);
      uint4 mp[10];
#pragma unroll
      for (int i = 0; i < 10; i++) mp[i] = tab[i * 32 + lane];
      mbar_wait(accbar, 0);
      const float4* ap = (const float4*)(smem_raw + ACC_STG) + (lane >> 2) * 32 + warp * 4 + (lane & 3);
#pragma unroll
      for (int i = 0; i < 10; i++) {
        const float4 av = ap[i * 256];
        xa[i] = bf2_add(xa[i], bf2_mul(mp[i].x, pack_bf16(av.x, av.y)));
        xb[i] = bf2_add(xb[i], bf2_mul(mp[i].x, pack_bf16(av.z, av.w)));
      }
      float4 st4 = ln_stats2(xa, xb);
      if (lane == 0) {
        float2* sp = (float2*)(smem_raw + 20480);
        sp[warp] = make_float2(st4.x, st4.y); sp[warp + 8] = make_float2(st4.z, st4.w);
      }
#pragma unroll
      for (int i = 0; i < 10; i++) {
        const float c0 = bf_lo(mp[i].y), c1 = bf_hi(mp[i].y), s0 = bf_lo(mp[i].z), s1 = bf_hi(mp[i].z);
        xa[i] = pack_bf16(fmaf(fmaf(bf_lo(xa[i]), st4.x, st4.y), c0, s0), fmaf(fmaf(bf_hi(xa[i]), st4.x, st4.y), c1, s1));
        xb[i] = pack_bf16(fmaf(fmaf(bf_lo(xb[i]), st4.z, st4.w), c0, s0), fmaf(fmaf(bf_hi(xb[i]), st4.z, st4.w), c1, s1));
      }
      st4 = ln_stats2(xa, xb);
      uint32_t* st = (uint32_t*)smem_raw + warp * 320 + lane;
#pragma unroll
      for (int i = 0; i < 10; i++) {
        st[i * 32] = pack_bf16(fmaf(bf_lo(xa[i]), st4.x, st4.y), fmaf(bf_hi(xa[i]), st4.x, st4.y));
        st[2560 + i * 32] = pack_bf16(fmaf(bf_lo(xb[i]), st4.z, st4.w), fmaf(bf_hi(xb[i]), st4.z, st4.w));
      }
      mbar_wait(xbar, 0);
      {
        const uint32_t rb = sbase + (wg ? XT1 : XT0) + (warp4 * 16 + (lane & 7) + ((lane >> 3) & 1) * 8) * 160 + (lane >> 4) * 16;
#pragma unroll
        for (int j = 0; j < 5; j++)
          asm volatile("ldmatrix.sync.aligned.m8n8.x4.shared.b16 {%0, %1, %2, %3}, [%4];"
                       : "=r"(x2r[4 * j]), "=r"(x2r[4 * j + 1]), "=r"(x2r[4 * j + 2]), "=r"(x2r[4 * j + 3]) : "r"(rb + j * 32) : "memory");
      }
      fence_proxy_async_smem();
      bar_sync(1, 256);
      if (tid == 0) {
        bulk_s2g(g_t + (size_t)(R * 128 + n * 16) * DM, sbase, 20480);
        bulk_s2g(g_st2 + (R * 128 + n * 16) * 2, sbase + 20480, 128);
        bulk_commit();
        bulk_wait<0>();
        flag_add(g_flag + (r64 + (n >> 2)) * 8 + (n & 3));
      }
      if (blockIdx.x < 5) g_modc[blockIdx.x * 256 + tid] = 0u;
      else if (blockIdx.x == 5 && tid < 48) g_cnt2[tid * 32] = 0;
      const float4* gp = (const float4*)g_acc + (size_t)((r64 + wg) * 4 + warp4) * 2560 + n * 320 + lane;
      float4 tv[10];
#pragma unroll
      for (int j = 0; j < 10; j++) tv[j] = __ldcg(gp + j * 32);
#pragma unroll
      for (int j = 0; j < 10; j++) {
        const uint32_t g2 = svp[j * 4 + (lane & 3)].x;
        x2r[2 * j] = bf2_add(x2r[2 * j], bf2_mul(g2, pack_bf16(tv[j].x, tv[j].y)));
        x2r[2 * j + 1] = bf2_add(x2r[2 * j + 1], bf2_mul(g2, pack_bf16(tv[j].z, tv[j].w)));
      }
    }
    Ring<PA_N> pA{0, 0};
    Ring<PB_N> pB{0, 0};
    const uint32_t eA = mapa(emptyA(0), wg);
    auto rearm = [&](int s) { if ((tid & 127) == 0) mbar_expect_tx(fullA(s, wg), 8192); };
    auto relA = [&](int s) { rearm(s); if (lane == 0) mbar_arrive_cluster(eA + s * 8); };
    auto relB = [&](int s) { if (lane == 0) mbar_arrive(emptyB(s)); };
    auto gemm80 = [&](float (&acc)[40]) {
      int prevA = -1, prevB = -1;
#pragma unroll 1
      for (int i = 0; i < 5; i++) {
        const int sB = pB.slot; mbar_wait(fullB(sB), pB.phase); pB.next();
#pragma unroll
        for (int hf = 0; hf < 2; hf++) {
          const int sA = pA.slot; mbar_wait(fullA(sA, wg), pA.phase); pA.next();
          const uint32_t dA = mkdesc(sbase + sA * PA_SZ + wg * 8192, 16);
          const uint32_t dB = mkdesc(sbase + PB_OFF + sB * PB_SZ + hf * 10240, 16);
          wg_fence();
#pragma unroll
          for (int kk = 0; kk < 4; kk++) wgmma_m64n80k16_ss_tb0(acc, dA + kk * 2, dB + kk * 2, (i | hf | kk) != 0);
          wg_commit();
          wg_wait<1>();
          if (prevA >= 0) relA(prevA);
          if (hf == 0 && prevB >= 0) relB(prevB);
          prevA = sA;
        }
        prevB = sB;
      }
      wg_wait<0>();
      fence_regs(acc);
      relA(prevA); relB(prevB);
      bar_sync(2 + wg, 128);
    };
    const uint32_t stg = sbase + wg * 8192;
    auto publish = [&](int ev) { fence_proxy_async_smem(); __syncwarp(); if (lane == 0) mbar_arrive(stgbar(wg, ev)); };
    auto stage80 = [&](const uint32_t (&v)[20], int ev) {
      const uint32_t rb = stg + (ev == 5 ? 3 * PA_SZ : 0) + (warp4 >> 1) * PA_SZ + ((warp4 & 1) * 16 + (lane & 7) + ((lane >> 3) & 1) * 8) * 160 + (lane >> 4) * 16;
#pragma unroll
      for (int j = 0; j < 5; j++) stmatrix_x4(rb + j * 32, v[4 * j], v[4 * j + 1], v[4 * j + 2], v[4 * j + 3]);
      publish(ev);
    };
    float acc[40];
    uint32_t v[20], x1r[20];
    gemm80(acc);
#pragma unroll
    for (int j = 0; j < 20; j++) v[j] = gelu_pair(acc[2 * j], acc[2 * j + 1]);
    stage80(v, 0);
    {
      const float2 sA = __ldcg((const float2*)g_st2 + row0), sB = __ldcg((const float2*)g_st2 + row0 + 8);
#pragma unroll
      for (int j = 0; j < 20; j++) {
        const uint4 mq = svp[(j >> 1) * 4 + (lane & 3)];
        const float2 st = (j & 1) ? sB : sA;
        x1r[j] = pack_bf16(fmaf(fmaf(bf_lo(x2r[j]), st.x, st.y), bf_lo(mq.y), bf_lo(mq.z)), fmaf(fmaf(bf_hi(x2r[j]), st.x, st.y), bf_hi(mq.y), bf_hi(mq.z)));
      }
      fence_regs_u(x1r);
    }
    gemm80(acc);
    {
      float s0 = 0.f, q0 = 0.f, s1 = 0.f, q1 = 0.f;
#pragma unroll
      for (int j = 0; j < 20; j++) x1r[j] = bf2_add(x1r[j], pack_bf16(acc[2 * j], acc[2 * j + 1]));
      stage80(x1r, 1);
#pragma unroll
      for (int j = 0; j < 20; j++) {
        const float lo = bf_lo(x1r[j]), hi = bf_hi(x1r[j]);
        if (j & 1) { s1 += lo + hi; q1 = fmaf(lo, lo, fmaf(hi, hi, q1)); } else { s0 += lo + hi; q0 = fmaf(lo, lo, fmaf(hi, hi, q0)); }
      }
#pragma unroll
      for (int o = 1; o <= 2; o <<= 1) {
        s0 += __shfl_xor_sync(0xffffffffu, s0, o); q0 += __shfl_xor_sync(0xffffffffu, q0, o);
        s1 += __shfl_xor_sync(0xffffffffu, s1, o); q1 += __shfl_xor_sync(0xffffffffu, q1, o);
      }
      if ((lane & 3) == 0) {
        float2* sp = (float2*)(smem_raw + STAT_OFF + wg * 512) + warp4 * 16 + (lane >> 2);
        sp[0] = make_float2(s0, q0); sp[8] = make_float2(s1, q1);
      }
      publish(6);
    }
    {
      float ac3[96];
      int prevA = -1, prevB = -1;
#pragma unroll 1
      for (int kb = 0; kb < 10; kb++) {
        const int sB = pB.slot; mbar_wait(fullB(sB), pB.phase); pB.next();
        const int sA = pA.slot; mbar_wait(fullA(sA, wg), pA.phase); pA.next();
        const uint32_t dA = mkdesc(sbase + sA * PA_SZ + wg * 8192, 16);
        const uint32_t dB = mkdesc(sbase + PB_OFF + sB * PB_SZ, 8192);
        wg_fence();
#pragma unroll
        for (int kk = 0; kk < 4; kk++) wgmma_m64n192k16_ss_tb1(ac3, dA + kk * 2, dB + kk * 128, (kb | kk) != 0);
        wg_commit();
        wg_wait<1>();
        if (prevA >= 0) { relA(prevA); relB(prevB); }
        prevA = sA; prevB = sB;
      }
      const float2* sp = (const float2*)g_stats + (size_t)(lane & 3) * 2 * SEQ + row0;
      const float2 t0 = __ldcg(sp), t1 = __ldcg(sp + SEQ), t2 = __ldcg(sp + 8), t3 = __ldcg(sp + SEQ + 8);
      float s0 = t0.x + t1.x, q0 = t0.y + t1.y, s1 = t2.x + t3.x, q1 = t2.y + t3.y;
#pragma unroll
      for (int o = 1; o <= 2; o <<= 1) {
        s0 += __shfl_xor_sync(0xffffffffu, s0, o); q0 += __shfl_xor_sync(0xffffffffu, q0, o);
        s1 += __shfl_xor_sync(0xffffffffu, s1, o); q1 += __shfl_xor_sync(0xffffffffu, q1, o);
      }
      const float m0 = s0 * (1.0f / DM), m1 = s1 * (1.0f / DM);
      const float r0 = rsqrtf(fmaxf(q0 * (1.0f / DM) - m0 * m0, 0.f) + 1e-5f), r1 = rsqrtf(fmaxf(q1 * (1.0f / DM) - m1 * m1, 0.f) + 1e-5f);
      const float mr0 = -m0 * r0, mr1 = -m1 * r1;
      wg_wait<0>();
      fence_regs(ac3);
      rearm(prevA); relB(prevB);
      __syncwarp();
      if (lane < 3) mbar_arrive(empty4(3 + lane, wg));
      bar_sync(2 + wg, 128);
      const int row = warp4 * 16 + (lane & 7) + ((lane >> 3) & 1) * 8;
#pragma unroll
      for (int kk = 0; kk < 12; kk++) {
        uint32_t u[4];
#pragma unroll
        for (int hh = 0; hh < 2; hh++) {
          const float2 cs3 = *(const float2*)(sv + kk * 16 + hh * 8 + (lane & 3) * 2);
          const int i = kk * 8 + hh * 4;
          u[hh * 2] = gelu_pair(fmaf(ac3[i], r0, mr0 * cs3.x), fmaf(ac3[i + 1], r0, mr0 * cs3.y));
          u[hh * 2 + 1] = gelu_pair(fmaf(ac3[i + 2], r1, mr1 * cs3.x), fmaf(ac3[i + 3], r1, mr1 * cs3.y));
        }
        const int cidx = (kk & 3) * 2 + (lane >> 4);
        stmatrix_x4(stg + (kk >> 2) * PA_SZ + row * 128 + ((cidx ^ (row & 7)) << 4), u[0], u[1], u[2], u[3]);
        if ((kk & 3) == 3) publish(2 + (kk >> 2));
      }
    }
    {
      float ac4[80];
      bar_sync(2 + wg, 128);
      int prevA = -1, prevB = -1;
#pragma unroll 1
      for (int i = 0; i < 12; i++) {
        const int sB = pB.slot; mbar_wait(fullB(sB), pB.phase); pB.next();
        const int sA = i >= 6 ? i - 6 : i;
        if (i >= 3) mbar_wait(fullA(sA, wg), i < 9);
        const uint32_t dA = mkdesc(sbase + sA * PA_SZ + wg * 8192, 16);
        const uint32_t dB = mkdesc(sbase + PB_OFF + sB * PB_SZ, 16);
        wg_fence();
#pragma unroll
        for (int kk = 0; kk < 4; kk++) wgmma_m64n160k16_ss_tb0(ac4, dA + kk * 2, dB + kk * 2, (i | kk) != 0);
        wg_commit();
        wg_wait<1>();
        if (i >= 4 && i <= 6) rearm(prevA);
        if (lane == 0) {
          if (i >= 1 && i <= 6) mbar_arrive(empty4(prevA, wg));
          else if (i == 9) mbar_arrive_cluster(mapa(xfree(wg), rank ^ 1));
          if (prevB >= 0) mbar_arrive(emptyB(prevB));
        }
        prevA = sA; prevB = sB;
      }
      mbar_wait(xfree(wg), 0);
      wg_wait<0>();
      fence_regs(ac4);
      const uint32_t rbuf = mapa(stg + (tid & 127) * 16, rank ^ 1), rbar = mapa(xfull(wg), rank ^ 1);
#pragma unroll
      for (int j = 0; j < 10; j++) {
        const float s0 = rank ? ac4[4 * j] : ac4[40 + 4 * j], s1 = rank ? ac4[4 * j + 1] : ac4[41 + 4 * j];
        const float s2 = rank ? ac4[4 * j + 2] : ac4[42 + 4 * j], s3 = rank ? ac4[4 * j + 3] : ac4[43 + 4 * j];
        asm volatile("st.async.weak.shared::cluster.mbarrier::complete_tx::bytes.v4.f32 [%0], {%1, %2, %3, %4}, [%5];"
                     ::"r"(rbuf + (j >> 2) * PA_SZ + (j & 3) * 2048), "f"(s0), "f"(s1), "f"(s2), "f"(s3), "r"(rbar) : "memory");
      }
#pragma unroll
      for (int j = 0; j < 40; j++) acc[j] = rank ? ac4[40 + j] : ac4[j];
      bar_sync(2 + wg, 128);
      mbar_wait(xfull(wg), 0);
      const float4* lp = (const float4*)(smem_raw + wg * 8192) + (tid & 127);
#pragma unroll
      for (int j = 0; j < 10; j++) {
        const float4 o4 = lp[(j >> 2) * 1024 + (j & 3) * 128];
        acc[4 * j] += o4.x; acc[4 * j + 1] += o4.y; acc[4 * j + 2] += o4.z; acc[4 * j + 3] += o4.w;
      }
    }
#pragma unroll
    for (int j = 0; j < 20; j++) {
      const uint32_t z = bf2_add(x1r[j], pack_bf16(acc[2 * j], acc[2 * j + 1]));
      v[j] = bf2_add(x2r[j], bf2_mul(svp[(j >> 1) * 4 + (lane & 3)].w, z));
    }
    stage80(v, 5);
    __syncwarp();
    cluster_sync();
  }
}

typedef CUresult (*EncodeFn)(CUtensorMap*, CUtensorMapDataType, cuuint32_t, void*, const cuuint64_t*, const cuuint64_t*,
                             const cuuint32_t*, const cuuint32_t*, CUtensorMapInterleave, CUtensorMapSwizzle,
                             CUtensorMapL2promotion, CUtensorMapFloatOOBfill);
#define L2PROMO CU_TENSOR_MAP_L2_PROMOTION_L2_128B
static EncodeFn g_encode = nullptr;

static void make_2d(CUtensorMap* tm, const void* base, uint64_t cols, uint64_t rows, uint32_t boxc, uint32_t boxr, bool swz = true) {
  cuuint64_t dims[2] = {cols, rows};
  cuuint64_t strides[1] = {cols * 2};
  cuuint32_t box[2] = {boxc, boxr};
  cuuint32_t es[2] = {1, 1};
  g_encode(tm, CU_TENSOR_MAP_DATA_TYPE_BFLOAT16, 2, (void*)base, dims, strides, box, es, CU_TENSOR_MAP_INTERLEAVE_NONE,
           swz ? CU_TENSOR_MAP_SWIZZLE_128B : CU_TENSOR_MAP_SWIZZLE_NONE, L2PROMO, CU_TENSOR_MAP_FLOAT_OOB_FILL_NONE);
}
static void make_3d(CUtensorMap* tm, const void* base, uint64_t cols, uint64_t rows, uint32_t boxr, uint32_t nblk) {
  cuuint64_t dims[3] = {64, rows, cols / 64};
  cuuint64_t strides[2] = {cols * 2, 128};
  cuuint32_t box[3] = {64, boxr, nblk};
  cuuint32_t es[3] = {1, 1, 1};
  g_encode(tm, CU_TENSOR_MAP_DATA_TYPE_BFLOAT16, 3, (void*)base, dims, strides, box, es, CU_TENSOR_MAP_INTERLEAVE_NONE,
           CU_TENSOR_MAP_SWIZZLE_128B, L2PROMO, CU_TENSOR_MAP_FLOAT_OOB_FILL_NONE);
}
template <typename T> static void* sym_addr(T& sym) { void* p = nullptr; cudaGetSymbolAddress(&p, sym); return p; }

template <typename... KArgs, typename... Args>
static void launch_pdl(bool pdl, void (*kern)(KArgs...), int grid, int block, int smem, cudaStream_t st, Args... args) {
  cudaLaunchConfig_t cfg = {};
  cfg.gridDim = dim3(grid); cfg.blockDim = dim3(block); cfg.dynamicSmemBytes = smem; cfg.stream = st;
  cudaLaunchAttribute at[1];
  at[0].id = cudaLaunchAttributeProgrammaticStreamSerialization;
  at[0].val.programmaticStreamSerializationAllowed = 1;
  cfg.attrs = at; cfg.numAttrs = pdl ? 1 : 0;
  cudaLaunchKernelEx(&cfg, kern, KArgs(args)...);
}

extern "C" void kernel_launch(void* const* d_in, const int* in_sizes, int n_in, void* d_out, int out_size) {
  const bf16* x = (const bf16*)d_in[0];
  const bf16* kc = (const bf16*)d_in[1];
  const bf16* vc = (const bf16*)d_in[2];
  const bf16* wq = (const bf16*)d_in[3];
  const bf16* wo = (const bf16*)d_in[4];
  const bf16* w1 = (const bf16*)d_in[6];
  const bf16* w2 = (const bf16*)d_in[7];
  const bf16* w3 = (const bf16*)d_in[8];
  const bf16* w4 = (const bf16*)d_in[9];
  const bf16* c = (const bf16*)d_in[10];
  const bf16* w_mod = (const bf16*)d_in[11];
  bf16* out = (bf16*)d_out;

  if (!g_encode) {
    cudaDriverEntryPointQueryResult qr;
    void* fn = nullptr;
    cudaGetDriverEntryPoint("cuTensorMapEncodeTiled", &fn, cudaEnableDefault, &qr);
    g_encode = (EncodeFn)fn;
    cudaFuncSetAttribute(attn_kernel, cudaFuncAttributeMaxDynamicSharedMemorySize, ATT_SMEM);
    cudaFuncSetAttribute(post_kernel, cudaFuncAttributeMaxDynamicSharedMemorySize, POST_SMEM);
  }
  CUtensorMap tmH, tmWq, tmK, tmV, tmWo;
  PostMaps pm;
  make_2d(&tmH, sym_addr(g_h), DM, SEQ, 64, 128);
  make_3d(&tmWq, wq, NH * DH, DM, 64, 3);
  make_3d(&tmK, kc, DH, (uint64_t)NH * SEQ, 64, 3);
  make_3d(&tmV, vc, DH, (uint64_t)NH * SEQ, 64, 3);
  make_2d(&tmWo, wo, DM, NH * DH, 64, 192);
  make_2d(&pm.aT, sym_addr(g_t), DM, SEQ, 64, 64);
  make_2d(&pm.aG, (bf16*)sym_addr(g_g) + 2 * DM, DM, SEQ, 64, 64);
  make_2d(&pm.aX1, sym_addr(g_x1), DM, SEQ, 64, 64);
  make_2d(&pm.lX, x, DM, SEQ, 80, 32, false);
  make_3d(&pm.bW3, w3, FF, DM, 64, 3);
  make_2d(&pm.sG, sym_addr(g_g), DM, SEQ + 4, 80, 32, false);
  make_2d(&pm.sX1, sym_addr(g_x1), DM, SEQ, 80, 32, false);
  make_2d(&pm.sOut, out, DM, SEQ, 80, 32, false);

  cudaStream_t st = cudaStreamPerThread;
#define PDL_MASK 6
  SideArgs sa{w_mod, x, c, w1, w2, w3, w4};
  launch_pdl(false, attn_kernel, 128 + NSIDE, 384, ATT_SMEM, st, sa, tmH, tmWq, tmK, tmV, tmWo);
  launch_pdl(PDL_MASK & 4, post_kernel, 128, 384, POST_SMEM, st, x, pm);
}
```
